```python
import torch

def _softmax(x, axis=-1):
    return torch.softmax(x, dim=axis)
def _gelu(x):
    return torch.nn.functional.gelu(x, approximate="tanh")
def _silu(x):
    return torch.nn.functional.silu(x)
def _sigmoid(x):
    return torch.sigmoid(x)
def _layernorm(x, axis=-1, eps=1e-5):
    m = x.mean(dim=axis, keepdim=True)
    v = x.var(dim=axis, keepdim=True, unbiased=False)
    return (x - m) / torch.sqrt(v + eps)
def _scatter_add(tgt, idx, src, axis=0):
    return tgt.clone().index_add_(axis, idx, src)
def _segment_sum(src, seg, n):
    out = torch.zeros((n,) + src.shape[1:], dtype=src.dtype)
    return out.index_add_(0, seg, src)
def _pad(x, pw):
    flat = tuple(v for pair in reversed(pw) for v in pair)
    return torch.nn.functional.pad(x, flat)

kernel_name = 'standalone__ssm_conv_s4__prompt'

def setup_inputs():

    _w = (lambda a: (lambda t: t.to(torch.bfloat16) if t.is_floating_point() else t)(torch.as_tensor(a)))
    B, L, D, N = 1, 2048, 576, 128
    A_re = -(lambda _x: torch.exp(torch.as_tensor(_x)))((lambda *s: torch.randn(*s, dtype=torch.bfloat16) * 3.2)(D, N))
    A_im = torch.pi * (lambda *s: torch.randn(*s, dtype=torch.bfloat16) * 0.05)(D, N)
    B_re = (lambda *s: torch.randn(*s, dtype=torch.bfloat16) * 0.1)(D, N)
    B_im = (lambda *s: torch.randn(*s, dtype=torch.bfloat16) * 0.1)(D, N)
    C_re = (lambda *s: torch.randn(*s, dtype=torch.bfloat16) * 0.1)(D, N)
    C_im = (lambda *s: torch.randn(*s, dtype=torch.bfloat16) * 0.1)(D, N)
    log_dt = (lambda *s: torch.randn(*s, dtype=torch.bfloat16) * 0.05)(D) * 0.5 - 4.0
    Dskip = (lambda *s: torch.randn(*s, dtype=torch.bfloat16) * 0.05)(D)
    return {
        "u": _w((lambda *s: torch.randn(*s, dtype=torch.bfloat16) * 0.05)(B, L, D)),
        "A_re": _w(A_re),
        "A_im": _w(A_im),
        "B_re": _w(B_re),
        "B_im": _w(B_im),
        "C_re": _w(C_re),
        "C_im": _w(C_im),
        "log_dt": _w(log_dt),
        "Dskip": _w(Dskip),
    }

def reference(u, A_re, A_im, B_re, B_im, C_re, C_im, log_dt, Dskip):
    Bsz, L, D = u.shape
    dt = torch.exp(log_dt)[:, None]
    A = A_re + 1j * A_im
    Bc = B_re + 1j * B_im
    Cc = C_re + 1j * C_im
    logdA = dt * A
    dB = dt * Bc
    l = (lambda x, dt: x.to(dt))(torch.arange(L), A_re.dtype)
    P = torch.exp(logdA[:, :, None] * l[None, None, :])
    K = torch.einsum("dn,dnl,dn->dl", Cc, P, dB).real
    L2 = 2 * L
    Kp = _pad(K, ((0, 0), (0, L)))
    up = (lambda x, *d: x.permute(*d))(u, 0, 2, 1)
    up = _pad(up, ((0, 0), (0, 0), (0, L)))
    Kf = (lambda x, axes=(-2,-1): torch.fft.rfft2(x.float(), dim=axes))(Kp[:, None, :], axes=(-2, -1))
    Uf = (lambda x, axes=(-2,-1): torch.fft.rfft2(x.float(), dim=axes))(up[:, :, None, :], axes=(-2, -1))
    Yf = Uf * Kf[None, :, :, :]
    y = (lambda x, s, axes=(-2,-1): torch.fft.irfft2(x, s=s, dim=axes).to(torch.bfloat16))(Yf, (1, L2), axes=(-2, -1))[:, :, 0, :L]
    y = (lambda x, *d: x.permute(*d))(y, 0, 2, 1) + u * Dskip[None, None, :]
    return y
```

```cpp
#include <cuda_runtime.h>
#include <cuda_bf16.h>
#include <cuda_fp16.h>
#include <stdint.h>

namespace {

constexpr int L_ = 2048, D_ = 576, N_ = 128;
constexpr int CL = 6;
constexpr int NSLOT = 6;
constexpr int NT = 512;
constexpr int NCW = 12;

constexpr int U_Z = 1056;
constexpr int U_STRIDE = 5280;
constexpr int U_OFF = 0;
constexpr int TAB_F = 0;
constexpr int TAB_D = 2240;
constexpr int TAB_2E = 4480;
constexpr int TAB_2O = 4736;
constexpr int TAB_3 = 4992;
constexpr int TAB_S = 5664;
constexpr int TAB_STRIDE = 5696;
constexpr int TAB_OFF = U_OFF + NSLOT * U_STRIDE;
constexpr int R_X5 = 0;
constexpr int R_X3 = 3360;
constexpr int R_X9 = 6720;
constexpr int R_X7 = R_X9 + 2048;
constexpr int R_XV = R_X7 + 2048;
constexpr int R_ZR = R_XV + 2064;
constexpr int R_P = R_XV + 2080;
constexpr int R_STRIDE = 21248;
constexpr int R_OFF = TAB_OFF + NSLOT * TAB_STRIDE;
constexpr int KG_PITCH = 272;
constexpr int KG_SEED = 21;
constexpr int KG_FAC = 29 * KG_PITCH;
constexpr int KG_SLICE = 8960;
constexpr int KG_KD = 2048;
constexpr int KG_K2E = KG_SLICE + 2048;
constexpr int KG_K2O = KG_K2E + 512;
constexpr int KG_T3 = KG_K2O + 512;
constexpr int KG_SC = KG_T3 + 672;
constexpr int YIN_PITCH = 736;
constexpr int YIN_OFF = R_OFF + NSLOT * R_STRIDE;
constexpr int MB_OFF = YIN_OFF + 32 * YIN_PITCH;
constexpr int MB_U = MB_OFF, MB_Y = MB_OFF + 8, MB_KD = MB_OFF + 16, MB_WD = MB_KD + 8 * NSLOT;
constexpr int SMEM_BYTES = MB_OFF + 128;

__device__ __forceinline__ uint32_t smem_u32(const void* p) { return (uint32_t)__cvta_generic_to_shared(p); }
__device__ __forceinline__ uint32_t mapa(uint32_t addr, uint32_t rank) {
    uint32_t r; asm volatile("mapa.shared::cluster.u32 %0, %1, %2;" : "=r"(r) : "r"(addr), "r"(rank)); return r;
}
__device__ __forceinline__ void mbar_init(uint32_t bar, uint32_t cnt) {
    asm volatile("mbarrier.init.shared::cta.b64 [%0], %1;" ::"r"(bar), "r"(cnt) : "memory");
}
__device__ __forceinline__ void mbar_arrive(uint32_t bar) {
    asm volatile("mbarrier.arrive.shared::cta.b64 _, [%0];" ::"r"(bar) : "memory");
}
__device__ __forceinline__ void mbar_arrive_tx(uint32_t bar, uint32_t bytes) {
    asm volatile("mbarrier.arrive.expect_tx.shared::cta.b64 _, [%0], %1;" ::"r"(bar), "r"(bytes) : "memory");
}
__device__ __forceinline__ void mbar_wait(uint32_t bar, uint32_t parity) {
    uint32_t ok; int it = 0;
    do {
        asm volatile("{\n.reg .pred p;\nmbarrier.try_wait.parity.shared::cta.b64 p, [%1], %2;\nselp.u32 %0, 1, 0, p;\n}"
                     : "=r"(ok) : "r"(bar), "r"(parity) : "memory");
        if (++it > (1 << 22)) __trap();
    } while (!ok);
}
__device__ __forceinline__ void pair_bar(int id) { asm volatile("bar.sync %0, 64;" ::"r"(id) : "memory"); }
__device__ __forceinline__ void ldsm4(uint32_t& r0, uint32_t& r1, uint32_t& r2, uint32_t& r3, uint32_t a) {
    asm volatile("ldmatrix.sync.aligned.m8n8.x4.shared.b16 {%0,%1,%2,%3}, [%4];" : "=r"(r0), "=r"(r1), "=r"(r2), "=r"(r3) : "r"(a) : "memory");
}
__device__ __forceinline__ void ldsm4t(uint32_t& r0, uint32_t& r1, uint32_t& r2, uint32_t& r3, uint32_t a) {
    asm volatile("ldmatrix.sync.aligned.m8n8.x4.trans.shared.b16 {%0,%1,%2,%3}, [%4];" : "=r"(r0), "=r"(r1), "=r"(r2), "=r"(r3) : "r"(a) : "memory");
}
__device__ __forceinline__ void ldsm2t(uint32_t& r0, uint32_t& r1, uint32_t a) {
    asm volatile("ldmatrix.sync.aligned.m8n8.x2.trans.shared.b16 {%0,%1}, [%2];" : "=r"(r0), "=r"(r1) : "r"(a) : "memory");
}
__device__ __forceinline__ void stsm4(uint32_t a, uint32_t r0, uint32_t r1, uint32_t r2, uint32_t r3) {
    asm volatile("stmatrix.sync.aligned.m8n8.x4.shared.b16 [%0], {%1,%2,%3,%4};" ::"r"(a), "r"(r0), "r"(r1), "r"(r2), "r"(r3) : "memory");
}
__device__ __forceinline__ void mma_bf16(float* c, uint32_t a0, uint32_t a1, uint32_t a2, uint32_t a3, uint32_t b0, uint32_t b1) {
    asm volatile("mma.sync.aligned.m16n8k16.row.col.f32.bf16.bf16.f32 {%0,%1,%2,%3},{%4,%5,%6,%7},{%8,%9},{%0,%1,%2,%3};"
                 : "+f"(c[0]), "+f"(c[1]), "+f"(c[2]), "+f"(c[3]) : "r"(a0), "r"(a1), "r"(a2), "r"(a3), "r"(b0), "r"(b1));
}
__device__ __forceinline__ void mma_f16(float* c, uint32_t a0, uint32_t a1, uint32_t a2, uint32_t a3, uint32_t b0, uint32_t b1) {
    asm volatile("mma.sync.aligned.m16n8k16.row.col.f32.f16.f16.f32 {%0,%1,%2,%3},{%4,%5,%6,%7},{%8,%9},{%0,%1,%2,%3};"
                 : "+f"(c[0]), "+f"(c[1]), "+f"(c[2]), "+f"(c[3]) : "r"(a0), "r"(a1), "r"(a2), "r"(a3), "r"(b0), "r"(b1));
}
__device__ __forceinline__ uint32_t lds32(uint32_t a) { uint32_t v; asm volatile("ld.shared.u32 %0, [%1];" : "=r"(v) : "r"(a) : "memory"); return v; }
__device__ __forceinline__ float lds32f(uint32_t a) { float v; asm volatile("ld.shared.f32 %0, [%1];" : "=f"(v) : "r"(a) : "memory"); return v; }
__device__ __forceinline__ float2 lds64f(uint32_t a) { float2 v; asm volatile("ld.shared.v2.f32 {%0,%1}, [%2];" : "=f"(v.x), "=f"(v.y) : "r"(a) : "memory"); return v; }
__device__ __forceinline__ uint2 lds64(uint32_t a) { uint2 v; asm volatile("ld.shared.v2.u32 {%0,%1}, [%2];" : "=r"(v.x), "=r"(v.y) : "r"(a) : "memory"); return v; }
__device__ __forceinline__ uint4 lds128(uint32_t a) { uint4 v; asm volatile("ld.shared.v4.u32 {%0,%1,%2,%3}, [%4];" : "=r"(v.x), "=r"(v.y), "=r"(v.z), "=r"(v.w) : "r"(a) : "memory"); return v; }
__device__ __forceinline__ float4 lds128f(uint32_t a) { float4 v; asm volatile("ld.shared.v4.f32 {%0,%1,%2,%3}, [%4];" : "=f"(v.x), "=f"(v.y), "=f"(v.z), "=f"(v.w) : "r"(a) : "memory"); return v; }
__device__ __forceinline__ void sts32(uint32_t a, uint32_t v) { asm volatile("st.shared.u32 [%0], %1;" ::"r"(a), "r"(v) : "memory"); }
__device__ __forceinline__ void sts32f(uint32_t a, float v) { asm volatile("st.shared.f32 [%0], %1;" ::"r"(a), "f"(v) : "memory"); }
__device__ __forceinline__ void sts64f(uint32_t a, float x, float y) { asm volatile("st.shared.v2.f32 [%0], {%1,%2};" ::"r"(a), "f"(x), "f"(y) : "memory"); }
__device__ __forceinline__ void sts128(uint32_t a, uint4 v) { asm volatile("st.shared.v4.u32 [%0], {%1,%2,%3,%4};" ::"r"(a), "r"(v.x), "r"(v.y), "r"(v.z), "r"(v.w) : "memory"); }
__device__ __forceinline__ void sts128f(uint32_t a, float x, float y, float z, float w) { asm volatile("st.shared.v4.f32 [%0], {%1,%2,%3,%4};" ::"r"(a), "f"(x), "f"(y), "f"(z), "f"(w) : "memory"); }

__device__ __forceinline__ uint32_t pack_bf16(float lo, float hi) {
    uint32_t r; asm("cvt.rn.bf16x2.f32 %0, %1, %2;" : "=r"(r) : "f"(hi), "f"(lo)); return r;
}
__device__ __forceinline__ uint32_t pack_f16(float lo, float hi) {
    uint32_t r; asm("cvt.rn.f16x2.f32 %0, %1, %2;" : "=r"(r) : "f"(hi), "f"(lo)); return r;
}
__device__ __forceinline__ uint32_t badd2(uint32_t a, uint32_t b) {
    __nv_bfloat162 r = __hadd2_rn(*reinterpret_cast<__nv_bfloat162*>(&a), *reinterpret_cast<__nv_bfloat162*>(&b));
    return *reinterpret_cast<uint32_t*>(&r);
}
__device__ __forceinline__ uint32_t bmul2(uint32_t a, uint32_t b) {
    __nv_bfloat162 r = __hmul2_rn(*reinterpret_cast<__nv_bfloat162*>(&a), *reinterpret_cast<__nv_bfloat162*>(&b));
    return *reinterpret_cast<uint32_t*>(&r);
}

struct H2C { __half2 r, i; };
__device__ __forceinline__ H2C hc_mul(const H2C& a, const H2C& b) {
    H2C o;
    o.r = __hfma2(a.r, b.r, __hneg2(__hmul2(a.i, b.i)));
    o.i = __hfma2(a.r, b.i, __hmul2(a.i, b.r));
    return o;
}
__device__ __forceinline__ H2C hc_mulc(const H2C& a, const H2C& e) {
    H2C o;
    o.r = __hfma2(a.r, e.r, __hmul2(a.i, e.i));
    o.i = __hfma2(a.i, e.r, __hneg2(__hmul2(a.r, e.i)));
    return o;
}
__device__ __forceinline__ uint32_t h2u(__half2 h) { return *reinterpret_cast<uint32_t*>(&h); }
__device__ __forceinline__ __half2 u2h(uint32_t u) { return *reinterpret_cast<__half2*>(&u); }
__device__ __forceinline__ float2 csq(float2 a) { return make_float2(fmaf(a.x, a.x, -a.y * a.y), (a.x + a.x) * a.y); }
__device__ __forceinline__ H2C hpack(float2 a, float2 b) { H2C o; o.r = u2h(pack_f16(a.x, b.x)); o.i = u2h(pack_f16(a.y, b.y)); return o; }
__device__ __forceinline__ float ex2f(float x) { float r; asm("ex2.approx.ftz.f32 %0, %1;" : "=f"(r) : "f"(x)); return r; }

__device__ __forceinline__ float bf_lo(uint32_t v) { return __uint_as_float(v << 16); }
__device__ __forceinline__ float bf_hi(uint32_t v) { return __uint_as_float(v & 0xffff0000u); }

__device__ __forceinline__ int grp_start(int r) { return r == 0 ? 0 : r == 1 ? 43 : r == 2 ? 86 : r == 3 ? 129 : r == 4 ? 172 : r == 5 ? 214 : 256; }
__device__ __forceinline__ int ubyte(int t) { return 2 * t + 16 * (t >> 8); }

__device__ __forceinline__ void exp_pair(float zr2  , float ph, float pl, float mult, float2& E) {
    float p = ph * mult;
    float r = (p - rintf(p)) + pl * mult;
    float ang = r * 6.283185307179586f;
    float m = ex2f(zr2 * mult);
    E.x = m * __cosf(ang);
    E.y = m * __sinf(ang);
}

__device__ __forceinline__ void kgen(uint32_t R, uint32_t TB, int h, int lane, int slot, int ch,
                                     const uint32_t* __restrict__ pv  , float ldt, uint32_t mb_kd)
{
    const int g = lane >> 2, q = lane & 3;
    const uint32_t S = R + h * KG_SLICE;
    float dt;
    {
        float e = expf(ldt);
        uint32_t b = __float_as_uint(e);
        int low = (int)(b & 0xffffu) - 0x8000;
        if (low >= -4 && low <= 4) e = (float)exp((double)ldt);
        dt = __bfloat162float(__float2bfloat16_rn(e));
    }
    float zr[2], zi[2]; float2 cb[2];
    #pragma unroll
    for (int k = 0; k < 2; k++) {
        float are = k ? bf_hi(pv[0]) : bf_lo(pv[0]);
        float aim = k ? bf_hi(pv[1]) : bf_lo(pv[1]);
        float bre = k ? bf_hi(pv[2]) : bf_lo(pv[2]);
        float bim = k ? bf_hi(pv[3]) : bf_lo(pv[3]);
        float cre = k ? bf_hi(pv[4]) : bf_lo(pv[4]);
        float cim = k ? bf_hi(pv[5]) : bf_lo(pv[5]);
        zr[k] = dt * are; zi[k] = dt * aim;
        float dbr = dt * bre, dbi = dt * bim;
        cb[k].x = fmaf(cre, dbr, -cim * dbi);
        cb[k].y = fmaf(cre, dbi, cim * dbr);
    }
    float gmax = fmaxf(zr[0], zr[1]);
    float cmax = fmaxf(fmaxf(fabsf(cb[0].x), fabsf(cb[0].y)), fmaxf(fabsf(cb[1].x), fabsf(cb[1].y)));
    #pragma unroll
    for (int o = 16; o; o >>= 1) {
        gmax = fmaxf(gmax, __shfl_xor_sync(0xffffffffu, gmax, o));
        cmax = fmaxf(cmax, __shfl_xor_sync(0xffffffffu, cmax, o));
    }
    gmax = fmaxf(gmax, 0.f);
    int ex = (int)((__float_as_uint(cmax) >> 23) & 0xff);
    ex = min(max(ex, 30), 230);
    const float sc = __uint_as_float((uint32_t)(127 + 10 + 127 - ex) << 23);
    const float isc = __uint_as_float((uint32_t)(ex - 10) << 23);

    float2 E1[2], E256[2];
    #pragma unroll
    for (int k = 0; k < 2; k++) {
        const float C1 = 0.15915494309189535f;
        const float C2 = (float)(0.15915494309189533576888 - (double)0.15915494309189535f);
        float ph = zi[k] * C1;
        float pl = fmaf(zi[k], C1, -ph) + zi[k] * C2;
        float z2 = (zr[k] - gmax) * 1.4426950408889634f;
        exp_pair(z2, ph, pl, 1.f, E1[k]);
        exp_pair(z2, ph, pl, 256.f, E256[k]);
    }
    const uint32_t wr = S + lane * 4;
    auto put = [&](int row, const H2C& v) { sts32(wr + row * KG_PITCH, h2u(v.r)); sts32(wr + row * KG_PITCH + 128, h2u(v.i)); };
    float2 a[2];
    H2C h1 = hpack(E1[0], E1[1]);
    a[0] = csq(E1[0]); a[1] = csq(E1[1]); H2C h2 = hpack(a[0], a[1]);
    a[0] = csq(a[0]); a[1] = csq(a[1]); H2C h4 = hpack(a[0], a[1]);
    { H2C h0; h0.r = u2h(0x3c003c00u); h0.i = u2h(0u); put(0, h0); }
    put(1, h1); put(2, h2); put(4, h4);
    H2C h3 = hc_mul(h1, h2); put(3, h3);
    put(5, hc_mul(h4, h1));
    H2C h6 = hc_mul(h4, h2); put(6, h6);
    put(7, hc_mul(h4, h3));
    a[0] = csq(a[0]); a[1] = csq(a[1]); H2C h8 = hpack(a[0], a[1]);
    a[0] = csq(a[0]); a[1] = csq(a[1]); H2C h16 = hpack(a[0], a[1]);
    a[0] = csq(a[0]); a[1] = csq(a[1]); H2C h32 = hpack(a[0], a[1]);
    a[0] = csq(a[0]); a[1] = csq(a[1]); H2C h64 = hpack(a[0], a[1]);
    a[0] = csq(a[0]); a[1] = csq(a[1]); H2C h128 = hpack(a[0], a[1]);
    H2C h192 = hc_mul(h128, h64);
    {
        uint32_t fa = S + KG_FAC + lane * 32;
        sts128(fa, make_uint4(h2u(h64.r), h2u(h64.i), h2u(h128.r), h2u(h128.i)));
        asm volatile("st.shared.v2.u32 [%0], {%1,%2};" ::"r"(fa + 16), "r"(h2u(h192.r)), "r"(h2u(h192.i)) : "memory");
    }
    H2C h256 = hpack(E256[0], E256[1]);
    put(8, h256); put(9, hc_mul(h256, h2)); put(10, hc_mul(h256, h4)); put(11, hc_mul(h256, h6));
    a[0] = csq(E256[0]); a[1] = csq(E256[1]); H2C h512 = hpack(a[0], a[1]);
    H2C h768 = hc_mul(h512, h256);
    put(12, h512); put(13, hc_mul(h512, h4)); put(14, h768); put(15, hc_mul(h768, h4));
    a[0] = csq(a[0]); a[1] = csq(a[1]); H2C h1024 = hpack(a[0], a[1]);
    put(16, h1024); put(17, hc_mul(h1024, h256)); put(18, hc_mul(h1024, h512)); put(19, hc_mul(h1024, h768));
    a[0] = csq(a[0]); a[1] = csq(a[1]); put(20, hpack(a[0], a[1]));
    {
        float2 c0 = make_float2(cb[0].x * sc, -cb[0].y * sc), c1 = make_float2(cb[1].x * sc, -cb[1].y * sc);
        H2C s0 = hpack(c0, c1);
        H2C s1 = hc_mulc(s0, h8), s2 = hc_mulc(s0, h16), s4 = hc_mulc(s0, h32);
        H2C s3 = hc_mulc(s1, h16);
        put(KG_SEED + 0, s0); put(KG_SEED + 1, s1); put(KG_SEED + 2, s2); put(KG_SEED + 3, s3); put(KG_SEED + 4, s4);
        put(KG_SEED + 5, hc_mulc(s1, h32)); put(KG_SEED + 6, hc_mulc(s2, h32)); put(KG_SEED + 7, hc_mulc(s3, h32));
    }
    __syncwarp();
    float acc[2][3][4];
    #pragma unroll
    for (int i = 0; i < 2; i++)
        #pragma unroll
        for (int j = 0; j < 3; j++)
            #pragma unroll
            for (int k = 0; k < 4; k++) acc[i][j][k] = 0.f;
    {
        const int mi = lane >> 3, r = lane & 7;
        uint32_t aA = S + ((mi >> 1) * 8 + r) * KG_PITCH + (mi & 1) * 128;
        int row2 = (mi >> 1) ? (KG_SEED + r) : min(16 + r, 20);
        uint32_t aB = S + row2 * KG_PITCH + (mi & 1) * 128;
        uint32_t aF = S + KG_FAC + q * 32;
        #pragma unroll
        for (int ks = 0; ks < 8; ks++) {
            uint32_t b00, b01, b10, b11, b20, b21, sr, si;
            ldsm4(b00, b01, b10, b11, aA + ks * 16);
            ldsm4(b20, b21, sr, si, aB + ks * 16);
            uint4 f0 = lds128(aF + ks * 128);
            uint2 f1 = lds64(aF + ks * 128 + 16);
            H2C s; s.r = u2h(sr); s.i = u2h(si);
            H2C f64; f64.r = u2h(f0.x); f64.i = u2h(f0.y);
            H2C f128; f128.r = u2h(f0.z); f128.i = u2h(f0.w);
            H2C f192; f192.r = u2h(f1.x); f192.i = u2h(f1.y);
            H2C t1 = hc_mulc(s, f64), t2 = hc_mulc(s, f128), t3 = hc_mulc(s, f192);
            mma_f16(acc[0][0], sr, h2u(t1.r), si, h2u(t1.i), b00, b01);
            mma_f16(acc[0][1], sr, h2u(t1.r), si, h2u(t1.i), b10, b11);
            mma_f16(acc[0][2], sr, h2u(t1.r), si, h2u(t1.i), b20, b21);
            mma_f16(acc[1][0], h2u(t2.r), h2u(t3.r), h2u(t2.i), h2u(t3.i), b00, b01);
            mma_f16(acc[1][1], h2u(t2.r), h2u(t3.r), h2u(t2.i), h2u(t3.i), b10, b11);
            mma_f16(acc[1][2], h2u(t2.r), h2u(t3.r), h2u(t2.i), h2u(t3.i), b20, b21);
        }
    }
    #pragma unroll
    for (int i = 0; i < 2; i++)
        #pragma unroll
        for (int j = 0; j < 3; j++)
            #pragma unroll
            for (int k = 0; k < 4; k++) acc[i][j][k] *= isc;
    if (gmax > 0.f) {
        #pragma unroll
        for (int i = 0; i < 2; i++)
            #pragma unroll
            for (int j = 0; j < 3; j++)
                #pragma unroll
                for (int k = 0; k < 4; k++) {
                    int gp = 16 * i + g + 8 * (k >> 1), c = 2 * q + (k & 1);
                    int l;
                    if (j == 0) l = 8 * gp + c;
                    else if (j == 1) l = (c < 4) ? 256 + 8 * gp + 2 * c : (c < 6 ? 512 + 8 * gp + 4 * (c - 4) : 768 + 8 * gp + 4 * (c - 6));
                    else l = 1024 + 256 * c + 8 * gp;
                    acc[i][j][k] *= expf(gmax * (float)l);
                }
    }
    __syncwarp();
    {
        uint32_t xa = S + lane * 16;
        if (h == 0) {
            #pragma unroll
            for (int j = 0; j < 3; j++) sts128f(xa + j * 512, acc[1][j][0], acc[1][j][1], acc[1][j][2], acc[1][j][3]);
        } else {
            #pragma unroll
            for (int j = 0; j < 3; j++) sts128f(xa + j * 512, acc[0][j][0], acc[0][j][1], acc[0][j][2], acc[0][j][3]);
        }
    }
    pair_bar(1 + slot);
    float v[3][4];
    {
        uint32_t xa = R + (1 - h) * KG_SLICE + lane * 16;
        #pragma unroll
        for (int j = 0; j < 3; j++) {
            float4 o = lds128f(xa + j * 512);
            v[j][0] = (h ? acc[1][j][0] : acc[0][j][0]) + o.x;
            v[j][1] = (h ? acc[1][j][1] : acc[0][j][1]) + o.y;
            v[j][2] = (h ? acc[1][j][2] : acc[0][j][2]) + o.z;
            v[j][3] = (h ? acc[1][j][3] : acc[0][j][3]) + o.w;
        }
    }
    {
        const uint32_t KD = R + KG_KD + 36 * 4;
        #pragma unroll
        for (int rr = 0; rr < 2; rr++) {
            int gp = 16 * h + g + 8 * rr;
            sts64f(KD + (8 * gp + 2 * q) * 4, v[0][2 * rr], v[0][2 * rr + 1]);
            if (q < 2) {
                int c = 256 + 8 * gp + 4 * q;
                if (c != 256) sts32f(KD + (c - 1) * 4, v[1][2 * rr]);
                sts64f(KD + c * 4, v[1][2 * rr], v[1][2 * rr]);
                sts32f(KD + (c + 2) * 4, v[1][2 * rr + 1]);
                sts32f(R + KG_T3 + (33 + 64 * q + gp) * 4, (q == 0 && gp == 0) ? 0.f : v[2][2 * rr]);
                sts32f(R + KG_T3 + (33 + 64 * q + 32 + gp) * 4, v[2][2 * rr + 1]);
                if (q == 0 && gp == 0) sts32f(R + KG_SC + 4, v[2][0]);
            } else {
                int i = 32 * (q - 2) + gp;
                sts32f(R + KG_K2E + (33 + i) * 4, v[1][2 * rr]);
                sts32f(R + KG_K2O + (33 + i) * 4, v[1][2 * rr + 1]);
                if (q == 2 && gp == 0) { sts32f(R + KG_T3 + (33 + 128) * 4, v[2][0]); sts32f(R + KG_SC, v[1][0]); }
            }
        }
        int t = h * 32 + lane;
        if (t < 36) sts32f(R + KG_KD + t * 4, 0.f);
        if (t < 37) sts32f(KD + (511 + t) * 4, 0.f);
        if (t < 33) {
            sts32f(R + KG_K2E + t * 4, 0.f); sts32f(R + KG_K2O + t * 4, 0.f); sts32f(R + KG_T3 + t * 4, 0.f);
        }
        if (t < 31) { sts32f(R + KG_K2E + (97 + t) * 4, 0.f); sts32f(R + KG_K2O + (97 + t) * 4, 0.f); }
        if (t < 6) sts32f(R + KG_T3 + (162 + t) * 4, 0.f);
    }
    pair_bar(1 + slot);
    {
        const uint32_t KD = R + KG_KD + 36 * 4;
        const float k512 = lds32f(R + KG_SC);
        const int t = h * 32 + lane;
        #pragma unroll
        for (int it = 0; it < 3; it++) {
            int i = t + 64 * it;
            if (i < 140) {
                int x0 = 4 * i - 32;
                float km = lds32f(KD + (x0 - 1) * 4);
                float4 k = lds128f(KD + x0 * 4);
                float wm = lds32f(KD + (x0 + 15) * 4);
                float4 w = lds128f(KD + (x0 + 16) * 4);
                if (x0 == 508) k.z -= k512;
                if (x0 == 492) w.z -= k512;
                float dm = wm - km, d0 = w.x - k.x, d1 = w.y - k.y, d2 = w.z - k.z, d3 = w.w - k.w;
                sts128(TB + TAB_F + i * 16, make_uint4(pack_bf16(k.x, km), pack_bf16(k.y, k.x), pack_bf16(k.z, k.y), pack_bf16(k.w, k.z)));
                sts128(TB + TAB_D + i * 16, make_uint4(pack_bf16(d0, dm), pack_bf16(d1, d0), pack_bf16(d2, d1), pack_bf16(d3, d2)));
            }
        }
        {
            int x = 2 * t - 32;
            float e0 = lds32f(R + KG_K2E + (33 + x) * 4), e1 = lds32f(R + KG_K2E + (32 + x) * 4);
            float o0 = lds32f(R + KG_K2O + (33 + x) * 4), o1 = lds32f(R + KG_K2O + (32 + x) * 4);
            sts32(TB + TAB_2E + t * 4, pack_bf16(e0, e1));
            sts32(TB + TAB_2O + t * 4, pack_bf16(o0, o1));
        }
        #pragma unroll
        for (int it = 0; it < 3; it++) {
            int idx = t + 64 * it;
            if (idx < 164) {
                int x = idx - 32;
                float e0 = lds32f(R + KG_T3 + (33 + x) * 4), e1 = lds32f(R + KG_T3 + (32 + x) * 4);
                sts32(TB + TAB_3 + idx * 4, pack_bf16(e0, e1));
            }
        }
        if (t == 0) { float k1024 = lds32f(R + KG_SC + 4); sts32(TB + TAB_S, pack_bf16(k1024, 0.f)); }
    }
    __syncwarp();
    if (lane == 0) mbar_arrive(mb_kd);
    pair_bar(1 + slot);
}

template <int H>
__device__ __forceinline__ void s01(uint32_t U, uint32_t TB, uint32_t P, int lane)
{
    const int g = lane >> 2, q = lane & 3;
    const uint32_t ub = U + U_Z + (lane & 7) * 528 + (lane >> 3) * 16;
    const uint32_t fb = TB + TAB_F + (32 + g - 2 * q) * 4;
    const uint32_t db = TB + TAB_D + (32 + g - 2 * q) * 4;
    float ap[4][4], aq[4][4], ar[4][4];
    #pragma unroll
    for (int e = 0; e < 4; e++)
        #pragma unroll
        for (int k = 0; k < 4; k++) { ap[e][k] = 0.f; aq[e][k] = 0.f; ar[e][k] = 0.f; }
    uint32_t x0[20][2], x1[20][2], xs[20][2];
    #pragma unroll
    for (int b = 0; b < 4; b++) {
        constexpr int dummy = 0; (void)dummy;
        const int i = 8 * H + 2 * b;
        const int off = 32 * i + 16 * (i >> 4);
        ldsm4(x0[b + 16][0], x0[b + 16][1], x1[b + 16][0], x1[b + 16][1], ub + off);
        xs[b + 16][0] = badd2(x0[b + 16][0], x1[b + 16][0]);
        xs[b + 16][1] = badd2(x0[b + 16][1], x1[b + 16][1]);
    }
    uint32_t dprev = lds32(db - 24 * 4);
    #pragma unroll
    for (int m = 0; m < 17; m++) {
        if (m > 0) {
            const int b = -m;
            const int i = 8 * H + 2 * b;
            const int off = 32 * i + 16 * (i >> 4);
            ldsm4(x0[b + 16][0], x0[b + 16][1], x1[b + 16][0], x1[b + 16][1], ub + off);
            xs[b + 16][0] = badd2(x0[b + 16][0], x1[b + 16][0]);
            xs[b + 16][1] = badd2(x0[b + 16][1], x1[b + 16][1]);
        }
        uint32_t fm = lds32(fb + (32 * m - 8) * 4), f0 = lds32(fb + (32 * m) * 4), fp = lds32(fb + (32 * m + 8) * 4);
        uint32_t d16 = lds32(db + (32 * m - 16) * 4), d8 = lds32(db + (32 * m - 8) * 4);
        uint32_t d0 = lds32(db + (32 * m) * 4), dp = lds32(db + (32 * m + 8) * 4);
        #pragma unroll
        for (int e = 0; e < 4; e++) mma_bf16(aq[e], d16, d8, dprev, d16, x1[e - m + 16][0], x1[e - m + 16][1]);
        #pragma unroll
        for (int e = 0; e < 4; e++) mma_bf16(ap[e], f0, fp, fm, f0, xs[e - m + 16][0], xs[e - m + 16][1]);
        #pragma unroll
        for (int e = 0; e < 4; e++) mma_bf16(ar[e], d0, dp, d8, d0, x0[e - m + 16][0], x0[e - m + 16][1]);
        dprev = dp;
    }
    const uint32_t pb = P + (520 * q + g) * 4;
    #pragma unroll
    for (int e = 0; e < 4; e++) {
        #pragma unroll
        for (int ph = 0; ph < 2; ph++) {
            const int J = 2 * (4 * H + e) + ph;
            const int sw = ((J >> 1) & 1) << 3;
            #pragma unroll
            for (int k = 0; k < 4; k++) {
                float val = ph ? ap[e][k] + ar[e][k] : ap[e][k] - aq[e][k];
                const int w = 256 * (k & 1) + 16 * J + ((8 * (k >> 1)) ^ sw);
                sts32f(pb + w * 4, val);
            }
        }
    }
}

__device__ __forceinline__ void s23_mma(uint32_t R, uint32_t TB, int p, int lane, float (&acc)[7][4])
{
    const int g = lane >> 2, q = lane & 3;
    #pragma unroll
    for (int i = 0; i < 7; i++)
        #pragma unroll
        for (int k = 0; k < 4; k++) acc[i][k] = 0.f;
    {
        uint32_t we[14], wo[14];
        const uint32_t fe = TB + TAB_2E + (16 + g - q) * 4;
        #pragma unroll
        for (int m = -3; m <= 10; m++) { we[m + 3] = lds32(fe + m * 16); wo[m + 3] = lds32(fe + 256 + m * 16); }
        const int mi = lane >> 3, r = lane & 7;
        const uint32_t xb = R + ((mi >> 1) ? R_X3 : R_X5) + (16 + p + (mi & 1) * 8 + r) * 16;
        #pragma unroll
        for (int s = -1; s <= 11; s++) {
            uint32_t e0, e1, o0, o1;
            ldsm4t(e0, e1, o0, o1, xb + s * 256);
            #pragma unroll
            for (int rho = -1; rho <= 5; rho++) {
                const int kap = s - 2 * rho + 4;
                if (kap >= 0 && kap <= 5 && kap >= 3 - 2 * rho) {
                    mma_bf16(acc[rho + 1], we[8 - 2 * kap + 3], we[10 - 2 * kap + 3], we[7 - 2 * kap + 3], we[9 - 2 * kap + 3], e0, e1);
                    mma_bf16(acc[rho + 1], wo[8 - 2 * kap + 3], wo[10 - 2 * kap + 3], wo[7 - 2 * kap + 3], wo[9 - 2 * kap + 3], o0, o1);
                }
            }
        }
    }
    {
        uint32_t w3[18];
        const uint32_t f3 = TB + TAB_3 + (32 + 1 + p + 2 * (g - q)) * 4;
        #pragma unroll
        for (int m = -3; m <= 14; m++) w3[m + 3] = lds32(f3 + m * 32);
        const int mi = lane >> 3, r = lane & 7;
        const int k = (mi & 1) * 8 + r;
        const uint32_t xb = R + ((((k + 1) & 1) == p) ? R_X9 : R_X7) + ((mi >> 1) * 16 + k) * 16;
        #pragma unroll
        for (int k3 = 0; k3 < 8; k3 += 2) {
            uint32_t b[4];
            ldsm4t(b[0], b[1], b[2], b[3], xb + k3 * 256);
            #pragma unroll
            for (int d = 0; d < 2; d++) {
                #pragma unroll
                for (int rho = 2; rho <= 5; rho++) {
                    const int s = 2 * (rho - 2) - (k3 + d);
                    if (s >= -1) mma_bf16(acc[rho + 1], w3[2 * s + 3], w3[2 * s + 2 + 3], w3[2 * s - 1 + 3], w3[2 * s + 1 + 3], b[2 * d], b[2 * d + 1]);
                }
            }
        }
    }
    {
        uint32_t kk = lds32(TB + TAB_S);
        uint32_t ad = (g == 2 * q) ? kk : ((g == 2 * q + 1) ? (kk << 16) : 0u);
        const int k = lane & 15;
        #pragma unroll
        for (int rho = 1; rho <= 5; rho++) {
            int row = 32 * rho - 64 + p + 2 * k;
            uint32_t a = (row < -1) ? (R + R_ZR) : (R + R_XV + (row + 1) * 16);
            uint32_t b0, b1;
            ldsm2t(b0, b1, a);
            mma_bf16(acc[rho + 1], ad, 0u, 0u, ad, b0, b1);
        }
    }
}

__device__ __forceinline__ void s23_final(uint32_t P, uint32_t ST, int p, int lane, float (&acc)[7][4], int ch)
{
    const int g = lane >> 2, q = lane & 3;
    const uint32_t pb = P + ((16 * g + 8 * p + 2 * q) ^ (((g >> 1) & 1) << 3)) * 4;
    uint32_t pk[8][2];
    #pragma unroll
    for (int rho = -2; rho <= 5; rho++) {
        #pragma unroll
        for (int hi = 0; hi < 2; hi++) {
            const int w = 512 + 256 * rho + 128 * hi + 8 * ((2 + rho) >> 1);
            float2 v = lds64f(pb + w * 4);
            if (rho >= -1) { v.x += acc[rho + 1][2 * hi]; v.y += acc[rho + 1][2 * hi + 1]; }
            pk[rho + 2][hi] = pack_bf16(v.x, v.y);
        }
    }
    const int mi = lane >> 3, r = lane & 7;
    const uint32_t sb = ST + 2 * (256 * (mi >> 1) + 128 * (mi & 1) + 16 * r + 8 * p) + 16 * (mi >> 1);
    #pragma unroll
    for (int i = 0; i < 8; i += 2) stsm4(sb + i * 528, pk[i][0], pk[i][1], pk[i + 1][0], pk[i + 1][1]);
}

__device__ __forceinline__ void wgen_row(uint32_t U, uint32_t R, int idx)
{
    const int tau = idx - 1;
    const int t0 = 8 * tau;
    uint4 A = lds128(U + U_Z + ubyte(t0 - 8)), B = lds128(U + U_Z + ubyte(t0)), C = lds128(U + U_Z + ubyte(t0 + 8));
    uint32_t E[11] = {A.x, A.y, A.z, A.w, B.x, B.y, B.z, B.w, C.x, C.y, 0u};
    E[10] = C.z;
    uint32_t O[10];
    #pragma unroll
    for (int k = 1; k < 10; k++) O[k] = __byte_perm(E[k], E[k + 1], 0x5432);
    uint32_t S2[10];
    #pragma unroll
    for (int k = 2; k < 10; k++) S2[k] = badd2(E[k], O[k]);
    uint32_t S4[8];
    #pragma unroll
    for (int k = 2; k < 8; k++) S4[k] = badd2(S2[k], S2[k + 1]);
    uint32_t S5[8];
    #pragma unroll
    for (int k = 3; k < 8; k++) S5[k] = badd2(S4[k], E[k + 2]);
    sts128(R + R_X5 + (16 + tau) * 16, make_uint4(S5[3], S5[4], S5[5], S5[6]));
    sts128(R + R_X3 + (16 + tau) * 16, make_uint4(badd2(S2[2], O[1]), badd2(S2[3], O[2]), badd2(S2[4], O[3]), badd2(S2[5], O[4])));
    if (idx < 129) {
        uint32_t xv[4], x9[4], x7[4];
        #pragma unroll
        for (int k = 2; k < 6; k++) {
            xv[k - 2] = badd2(S4[k], badd2(S2[k + 2], E[k + 3]));
            x9[k - 2] = badd2(S4[k], S5[k + 2]);
            x7[k - 2] = badd2(O[k], badd2(S4[k + 1], S2[k + 3]));
        }
        sts128(R + R_XV + idx * 16, make_uint4(xv[0], xv[1], xv[2], xv[3]));
        if (idx < 128) {
            sts128(R + R_X9 + idx * 16, make_uint4(x9[0], x9[1], x9[2], x9[3]));
            sts128(R + R_X7 + idx * 16, make_uint4(x7[0], x7[1], x7[2], x7[3]));
        }
    }
}

__global__ void __cluster_dims__(CL, 1, 1) __launch_bounds__(NT, 1)
ssm_kernel(const __nv_bfloat16* __restrict__ u, const __nv_bfloat16* __restrict__ A_re, const __nv_bfloat16* __restrict__ A_im,
           const __nv_bfloat16* __restrict__ B_re, const __nv_bfloat16* __restrict__ B_im, const __nv_bfloat16* __restrict__ C_re,
           const __nv_bfloat16* __restrict__ C_im, const __nv_bfloat16* __restrict__ log_dt, const __nv_bfloat16* __restrict__ Dsk,
           __nv_bfloat16* __restrict__ out)
{
    extern __shared__ __align__(128) unsigned char smem[];
    const uint32_t sb = smem_u32(smem);
    const int tid = threadIdx.x, lane = tid & 31, w = tid >> 5;
    uint32_t rank; asm("mov.u32 %0, %%cluster_ctarank;" : "=r"(rank));
    const int chbase = (blockIdx.x / CL) * 32;
    const int nslot = (rank < 2) ? 6 : 5;
    const int g0 = grp_start(rank), g1 = grp_start(rank + 1);
    const int ystart = ubyte(8 * g0), ybytes = ubyte(8 * g1 - 8) + 16 - ystart;

    if (w < NCW) {
        const int slot = w >> 1, h = w & 1;
        const bool act = slot < nslot;
        const int ch = chbase + rank + 6 * slot;
        uint32_t pv[6] = {0, 0, 0, 0, 0, 0}; float ldt = 0.f;
        if (act) {
            const int o = ch * N_ + 64 * h + 2 * lane;
            pv[0] = __ldg(reinterpret_cast<const uint32_t*>(A_re + o));
            pv[1] = __ldg(reinterpret_cast<const uint32_t*>(A_im + o));
            pv[2] = __ldg(reinterpret_cast<const uint32_t*>(B_re + o));
            pv[3] = __ldg(reinterpret_cast<const uint32_t*>(B_im + o));
            pv[4] = __ldg(reinterpret_cast<const uint32_t*>(C_re + o));
            pv[5] = __ldg(reinterpret_cast<const uint32_t*>(C_im + o));
            ldt = __bfloat162float(log_dt[ch]);
        }
        if (tid == 0) {
            mbar_init(sb + MB_U, 1);
            mbar_init(sb + MB_Y, 1 + nslot);
            for (int s = 0; s < NSLOT; s++) { mbar_init(sb + MB_KD + 8 * s, 2); mbar_init(sb + MB_WD + 8 * s, 4); }
            asm volatile("fence.mbarrier_init.release.cluster;" ::: "memory");
            mbar_arrive_tx(sb + MB_U, nslot * 4096);
            mbar_arrive_tx(sb + MB_Y, (32 - nslot) * ybytes);
        }
        const uint32_t U = sb + U_OFF + slot * U_STRIDE, TB = sb + TAB_OFF + slot * TAB_STRIDE, R = sb + R_OFF + slot * R_STRIDE;
        if (act) {
            for (int i = h * 32 + lane; i < U_Z / 16; i += 64) sts128(U + i * 16, make_uint4(0, 0, 0, 0));
        }
        __syncthreads();
        asm volatile("barrier.cluster.arrive.release.aligned;" ::: "memory");
        if (act) {
            kgen(R, TB, h, lane, slot, ch, pv, ldt, sb + MB_KD + 8 * slot);
            mbar_wait(sb + MB_U, 0);
            if (h == 0) s01<0>(U, TB, R + R_P, lane); else s01<1>(U, TB, R + R_P, lane);
            mbar_wait(sb + MB_WD + 8 * slot, 0);
            float acc[7][4];
            s23_mma(R, TB, h, lane, acc);
            pair_bar(1 + slot);
            s23_final(R + R_P, U + U_Z, h, lane, acc, ch);
            asm volatile("fence.proxy.async.shared::cta;" ::: "memory");
        }
        asm volatile("barrier.cluster.wait.acquire.aligned;" ::: "memory");
        if (act) {
            pair_bar(1 + slot);
            if (h == 0 && lane < CL) {
                const int r = lane;
                const int a0 = grp_start(r), a1 = grp_start(r + 1);
                const int st = ubyte(8 * a0), nb = ubyte(8 * a1 - 8) + 16 - st;
                if (r != (int)rank) {
                    uint32_t dst = mapa(sb + YIN_OFF + (rank + 6 * slot) * YIN_PITCH, r);
                    uint32_t mb = mapa(sb + MB_Y, r);
                    asm volatile("cp.async.bulk.shared::cluster.shared::cta.mbarrier::complete_tx::bytes [%0], [%1], %2, [%3];"
                                 ::"r"(dst), "r"(U + U_Z + st), "r"(nb), "r"(mb) : "memory");
                } else {
                    mbar_arrive(sb + MB_Y);
                }
            }
        }
    } else {
        const int it0 = tid - NCW * 32;
        uint4 ur[2][8];
        bool val[2]; int gam[2], chunk[2];
        #pragma unroll
        for (int k = 0; k < 2; k++) {
            int task = it0 + 128 * k;
            chunk[k] = (task >> 3) & 3;
            int gl = (task & 7) + 8 * (task >> 5);
            gam[k] = g0 + gl;
            val[k] = gam[k] < g1;
            if (val[k]) {
                const uint4* p = reinterpret_cast<const uint4*>(u + (size_t)(8 * gam[k]) * D_ + chbase + 8 * chunk[k]);
                #pragma unroll
                for (int r = 0; r < 8; r++) ur[k][r] = __ldg(p + r * (D_ / 8));
            }
        }
        uint4 dv[2];
        #pragma unroll
        for (int k = 0; k < 2; k++) dv[k] = __ldg(reinterpret_cast<const uint4*>(Dsk + chbase + 8 * chunk[k]));
        __syncthreads();
        asm volatile("barrier.cluster.arrive.release.aligned;" ::: "memory");
        asm volatile("barrier.cluster.wait.acquire.aligned;" ::: "memory");
        #pragma unroll
        for (int k = 0; k < 2; k++) {
            if (val[k]) {
                const int tb = ubyte(8 * gam[k]);
                #pragma unroll
                for (int e = 0; e < 8; e++) {
                    const uint32_t sel = (e & 1) ? 0x7632 : 0x5410;
                    const uint32_t* a = reinterpret_cast<const uint32_t*>(&ur[k][0]);
                    uint32_t o0 = __byte_perm(a[0 * 4 + (e >> 1)], a[1 * 4 + (e >> 1)], sel);
                    uint32_t o1 = __byte_perm(a[2 * 4 + (e >> 1)], a[3 * 4 + (e >> 1)], sel);
                    uint32_t o2 = __byte_perm(a[4 * 4 + (e >> 1)], a[5 * 4 + (e >> 1)], sel);
                    uint32_t o3 = __byte_perm(a[6 * 4 + (e >> 1)], a[7 * 4 + (e >> 1)], sel);
                    const int c = 8 * chunk[k] + e;
                    const int dr = c % 6, ds = c / 6;
                    uint32_t dst = mapa(sb + U_OFF + ds * U_STRIDE + U_Z + tb, dr);
                    uint32_t mb = mapa(sb + MB_U, dr);
                    asm volatile("st.async.weak.shared::cluster.mbarrier::complete_tx::bytes.v4.b32 [%0], {%1,%2,%3,%4}, [%5];"
                                 ::"r"(dst), "r"(o0), "r"(o1), "r"(o2), "r"(o3), "r"(mb) : "memory");
                }
                #pragma unroll
                for (int r = 0; r < 8; r++) {
                    ur[k][r].x = bmul2(ur[k][r].x, dv[k].x); ur[k][r].y = bmul2(ur[k][r].y, dv[k].y);
                    ur[k][r].z = bmul2(ur[k][r].z, dv[k].z); ur[k][r].w = bmul2(ur[k][r].w, dv[k].w);
                }
            }
        }
        mbar_wait(sb + MB_U, 0);
        for (int s = 0; s < nslot; s++) {
            const uint32_t U = sb + U_OFF + s * U_STRIDE, R = sb + R_OFF + s * R_STRIDE;
            mbar_wait(sb + MB_KD + 8 * s, 0);
            wgen_row(U, R, it0);
            if (it0 < 66) wgen_row(U, R, it0 + 128);
            else if (it0 < 66 + 15) sts128(R + R_X5 + (it0 - 66) * 16, make_uint4(0, 0, 0, 0));
            else if (it0 < 66 + 30) sts128(R + R_X3 + (it0 - 81) * 16, make_uint4(0, 0, 0, 0));
            else if (it0 == 96) sts128(R + R_ZR, make_uint4(0, 0, 0, 0));
            __syncwarp();
            if (lane == 0) mbar_arrive(sb + MB_WD + 8 * s);
        }
        mbar_wait(sb + MB_Y, 0);
        #pragma unroll
        for (int k = 0; k < 2; k++) {
            if (val[k]) {
                const int tb = ubyte(8 * gam[k]);
                uint4 yc[8];
                #pragma unroll
                for (int e = 0; e < 8; e++) {
                    const int c = 8 * chunk[k] + e;
                    const int dr = c % 6, ds = c / 6;
                    uint32_t a = (dr == (int)rank) ? (sb + U_OFF + ds * U_STRIDE + U_Z + tb) : (sb + YIN_OFF + c * YIN_PITCH + tb - ystart);
                    yc[e] = lds128(a);
                }
                uint4* po = reinterpret_cast<uint4*>(out + (size_t)(8 * gam[k]) * D_ + chbase + 8 * chunk[k]);
                #pragma unroll
                for (int r = 0; r < 8; r++) {
                    const uint32_t sel = (r & 1) ? 0x7632 : 0x5410;
                    const uint32_t* y = reinterpret_cast<const uint32_t*>(&yc[0]);
                    uint4 o;
                    o.x = badd2(__byte_perm(y[0 * 4 + (r >> 1)], y[1 * 4 + (r >> 1)], sel), ur[k][r].x);
                    o.y = badd2(__byte_perm(y[2 * 4 + (r >> 1)], y[3 * 4 + (r >> 1)], sel), ur[k][r].y);
                    o.z = badd2(__byte_perm(y[4 * 4 + (r >> 1)], y[5 * 4 + (r >> 1)], sel), ur[k][r].z);
                    o.w = badd2(__byte_perm(y[6 * 4 + (r >> 1)], y[7 * 4 + (r >> 1)], sel), ur[k][r].w);
                    po[r * (D_ / 8)] = o;
                }
            }
        }
    }
    asm volatile("barrier.cluster.arrive.release.aligned;" ::: "memory");
    asm volatile("barrier.cluster.wait.acquire.aligned;" ::: "memory");
}

}

extern "C" void kernel_launch(void* const* d_in, const int* in_sizes, int n_in, void* d_out, int out_size)
{
    static bool first = true;
    if (first) {
        first = false;
        cudaFuncSetAttribute(ssm_kernel, cudaFuncAttributeMaxDynamicSharedMemorySize, SMEM_BYTES);
    }
    ssm_kernel<<<108, NT, SMEM_BYTES, cudaStreamPerThread>>>(
        (const __nv_bfloat16*)d_in[0], (const __nv_bfloat16*)d_in[1], (const __nv_bfloat16*)d_in[2], (const __nv_bfloat16*)d_in[3],
        (const __nv_bfloat16*)d_in[4], (const __nv_bfloat16*)d_in[5], (const __nv_bfloat16*)d_in[6], (const __nv_bfloat16*)d_in[7],
        (const __nv_bfloat16*)d_in[8], (__nv_bfloat16*)d_out);
}
```

```cpp
#include <cuda_runtime.h>
#include <cuda_bf16.h>
#include <cuda_fp16.h>
#include <stdint.h>

namespace {

constexpr int L_ = 2048, D_ = 576, N_ = 128;

constexpr int U_Z = 544, U_ARR = 2720, U_SIZE = 5504;
constexpr int W_OFF = U_SIZE;
constexpr int X5_OFF = 0, XH5 = 1600, X3_OFF = 3200, X9_OFF = 6400, XH9 = 1088, X7_OFF = 8512, XV_OFF = 10624, W_SIZE = 12800;
constexpr int KS_OFF = W_OFF + W_SIZE;
constexpr int KS_HALF = 7936, KS_FAC = 7424, KS_SIZE = 15872, KG_SEED = 21;
constexpr int SLOT = KS_OFF + KS_SIZE;
constexpr int TE = 0 + 16;
constexpr int TQ = 288 + 16;
constexpr int TR = 456 + 16;
constexpr int CQ = 624 - 64;
constexpr int CR = 696 - 64;
constexpr int T2E = 768 + 16;
constexpr int T2O = 864 + 16;
constexpr int T3 = 960 + 32;
constexpr int TSC = 1124;
constexpr int P2_OFF = 4608, P2_PLANE = 816 * 4;

__device__ __forceinline__ uint32_t smem_u32(const void* p) { return (uint32_t)__cvta_generic_to_shared(p); }
__device__ __forceinline__ uint32_t mapa(uint32_t addr, uint32_t rank) {
    uint32_t r; asm volatile("mapa.shared::cluster.u32 %0, %1, %2;" : "=r"(r) : "r"(addr), "r"(rank)); return r;
}
__device__ __forceinline__ void mbar_init(uint32_t bar, uint32_t cnt) {
    asm volatile("mbarrier.init.shared::cta.b64 [%0], %1;" ::"r"(bar), "r"(cnt) : "memory");
}
__device__ __forceinline__ void mbar_arrive_tx(uint32_t bar, uint32_t bytes) {
    asm volatile("mbarrier.arrive.expect_tx.shared::cta.b64 _, [%0], %1;" ::"r"(bar), "r"(bytes) : "memory");
}
__device__ __forceinline__ void mbar_wait(uint32_t bar, uint32_t parity) {
    uint32_t ok; int it = 0;
    do {
        asm volatile("{\n.reg .pred p;\nmbarrier.try_wait.parity.shared::cta.b64 p, [%1], %2;\nselp.u32 %0, 1, 0, p;\n}"
                     : "=r"(ok) : "r"(bar), "r"(parity) : "memory");
        if (++it > (1 << 22)) __trap();
    } while (!ok);
}
__device__ __forceinline__ void nb_sync(int id) { asm volatile("bar.sync %0, 64;" ::"r"(id) : "memory"); }
__device__ __forceinline__ void nb_arrive(int id) { asm volatile("bar.arrive %0, 64;" ::"r"(id) : "memory"); }
__device__ __forceinline__ void ldsm4(uint32_t& r0, uint32_t& r1, uint32_t& r2, uint32_t& r3, uint32_t a) {
    asm volatile("ldmatrix.sync.aligned.m8n8.x4.shared.b16 {%0,%1,%2,%3}, [%4];" : "=r"(r0), "=r"(r1), "=r"(r2), "=r"(r3) : "r"(a) : "memory");
}
__device__ __forceinline__ void ldsm4t(uint32_t& r0, uint32_t& r1, uint32_t& r2, uint32_t& r3, uint32_t a) {
    asm volatile("ldmatrix.sync.aligned.m8n8.x4.trans.shared.b16 {%0,%1,%2,%3}, [%4];" : "=r"(r0), "=r"(r1), "=r"(r2), "=r"(r3) : "r"(a) : "memory");
}
__device__ __forceinline__ void ldsm2t(uint32_t& r0, uint32_t& r1, uint32_t a) {
    asm volatile("ldmatrix.sync.aligned.m8n8.x2.trans.shared.b16 {%0,%1}, [%2];" : "=r"(r0), "=r"(r1) : "r"(a) : "memory");
}
__device__ __forceinline__ void mma_bf16(float* c, uint32_t a0, uint32_t a1, uint32_t a2, uint32_t a3, uint32_t b0, uint32_t b1) {
    asm volatile("mma.sync.aligned.m16n8k16.row.col.f32.bf16.bf16.f32 {%0,%1,%2,%3},{%4,%5,%6,%7},{%8,%9},{%0,%1,%2,%3};"
                 : "+f"(c[0]), "+f"(c[1]), "+f"(c[2]), "+f"(c[3]) : "r"(a0), "r"(a1), "r"(a2), "r"(a3), "r"(b0), "r"(b1));
}
__device__ __forceinline__ void mma_sp(float* c, uint32_t a0, uint32_t a1, uint32_t a2, uint32_t a3, uint32_t b0, uint32_t b1, uint32_t b2, uint32_t b3, uint32_t e) {
    asm volatile("mma.sp::ordered_metadata.sync.aligned.m16n8k32.row.col.f32.bf16.bf16.f32 {%0,%1,%2,%3},{%4,%5,%6,%7},{%8,%9,%10,%11},{%0,%1,%2,%3},%12,0x0;"
                 : "+f"(c[0]), "+f"(c[1]), "+f"(c[2]), "+f"(c[3]) : "r"(a0), "r"(a1), "r"(a2), "r"(a3), "r"(b0), "r"(b1), "r"(b2), "r"(b3), "r"(e));
}
__device__ __forceinline__ void mma_f16(float* c, uint32_t a0, uint32_t a1, uint32_t a2, uint32_t a3, uint32_t b0, uint32_t b1) {
    asm volatile("mma.sync.aligned.m16n8k16.row.col.f32.f16.f16.f32 {%0,%1,%2,%3},{%4,%5,%6,%7},{%8,%9},{%0,%1,%2,%3};"
                 : "+f"(c[0]), "+f"(c[1]), "+f"(c[2]), "+f"(c[3]) : "r"(a0), "r"(a1), "r"(a2), "r"(a3), "r"(b0), "r"(b1));
}
__device__ __forceinline__ uint32_t lds32(uint32_t a) { uint32_t v; asm volatile("ld.shared.u32 %0, [%1];" : "=r"(v) : "r"(a) : "memory"); return v; }
__device__ __forceinline__ float lds32f(uint32_t a) { float v; asm volatile("ld.shared.f32 %0, [%1];" : "=f"(v) : "r"(a) : "memory"); return v; }
__device__ __forceinline__ float2 lds64f(uint32_t a) { float2 v; asm volatile("ld.shared.v2.f32 {%0,%1}, [%2];" : "=f"(v.x), "=f"(v.y) : "r"(a) : "memory"); return v; }
__device__ __forceinline__ uint2 lds64(uint32_t a) { uint2 v; asm volatile("ld.shared.v2.u32 {%0,%1}, [%2];" : "=r"(v.x), "=r"(v.y) : "r"(a) : "memory"); return v; }
__device__ __forceinline__ uint4 lds128(uint32_t a) { uint4 v; asm volatile("ld.shared.v4.u32 {%0,%1,%2,%3}, [%4];" : "=r"(v.x), "=r"(v.y), "=r"(v.z), "=r"(v.w) : "r"(a) : "memory"); return v; }
__device__ __forceinline__ void sts16(uint32_t a, uint16_t v) { asm volatile("st.shared.u16 [%0], %1;" ::"r"(a), "h"(v) : "memory"); }
__device__ __forceinline__ void sts32(uint32_t a, uint32_t v) { asm volatile("st.shared.u32 [%0], %1;" ::"r"(a), "r"(v) : "memory"); }
__device__ __forceinline__ void sts32f(uint32_t a, float v) { asm volatile("st.shared.f32 [%0], %1;" ::"r"(a), "f"(v) : "memory"); }
__device__ __forceinline__ void sts64(uint32_t a, uint32_t x, uint32_t y) { asm volatile("st.shared.v2.u32 [%0], {%1,%2};" ::"r"(a), "r"(x), "r"(y) : "memory"); }
__device__ __forceinline__ void sts64f(uint32_t a, float x, float y) { asm volatile("st.shared.v2.f32 [%0], {%1,%2};" ::"r"(a), "f"(x), "f"(y) : "memory"); }
__device__ __forceinline__ void sts128(uint32_t a, uint32_t x, uint32_t y, uint32_t z, uint32_t w) { asm volatile("st.shared.v4.u32 [%0], {%1,%2,%3,%4};" ::"r"(a), "r"(x), "r"(y), "r"(z), "r"(w) : "memory"); }

__device__ __forceinline__ uint32_t pack_bf16(float lo, float hi) {
    uint32_t r; asm("cvt.rn.bf16x2.f32 %0, %1, %2;" : "=r"(r) : "f"(hi), "f"(lo)); return r;
}
__device__ __forceinline__ uint16_t cvt_bf16(float v) { uint16_t r; asm("cvt.rn.bf16.f32 %0, %1;" : "=h"(r) : "f"(v)); return r; }
__device__ __forceinline__ uint32_t pack_f16(float lo, float hi) {
    uint32_t r; asm("cvt.rn.f16x2.f32 %0, %1, %2;" : "=r"(r) : "f"(hi), "f"(lo)); return r;
}
__device__ __forceinline__ uint32_t badd2(uint32_t a, uint32_t b) {
    __nv_bfloat162 r = __hadd2_rn(*reinterpret_cast<__nv_bfloat162*>(&a), *reinterpret_cast<__nv_bfloat162*>(&b));
    return *reinterpret_cast<uint32_t*>(&r);
}
__device__ __forceinline__ uint32_t bmul2(uint32_t a, uint32_t b) {
    __nv_bfloat162 r = __hmul2_rn(*reinterpret_cast<__nv_bfloat162*>(&a), *reinterpret_cast<__nv_bfloat162*>(&b));
    return *reinterpret_cast<uint32_t*>(&r);
}
__device__ __forceinline__ uint32_t shift1(uint32_t a, uint32_t b) { return __byte_perm(a, b, 0x5432); }

struct H2C { __half2 r, i; };
__device__ __forceinline__ H2C hc_mul(const H2C& a, const H2C& b) {
    H2C o;
    o.r = __hfma2(a.r, b.r, __hneg2(__hmul2(a.i, b.i)));
    o.i = __hfma2(a.r, b.i, __hmul2(a.i, b.r));
    return o;
}
__device__ __forceinline__ H2C hc_mulc(const H2C& a, const H2C& e) {
    H2C o;
    o.r = __hfma2(a.r, e.r, __hmul2(a.i, e.i));
    o.i = __hfma2(a.i, e.r, __hneg2(__hmul2(a.r, e.i)));
    return o;
}
__device__ __forceinline__ uint32_t h2u(__half2 h) { return *reinterpret_cast<uint32_t*>(&h); }
__device__ __forceinline__ __half2 u2h(uint32_t u) { return *reinterpret_cast<__half2*>(&u); }
__device__ __forceinline__ float2 csq(float2 a) { return make_float2(fmaf(a.x, a.x, -a.y * a.y), (a.x + a.x) * a.y); }
__device__ __forceinline__ H2C hpack(float2 a, float2 b) { H2C o; o.r = u2h(pack_f16(a.x, b.x)); o.i = u2h(pack_f16(a.y, b.y)); return o; }
__device__ __forceinline__ float ex2f(float x) { float r; asm("ex2.approx.ftz.f32 %0, %1;" : "=f"(r) : "f"(x)); return r; }
__device__ __forceinline__ float bf_lo(uint32_t v) { return __uint_as_float(v << 16); }
__device__ __forceinline__ float bf_hi(uint32_t v) { return __uint_as_float(v & 0xffff0000u); }

#define TL(i)
#define TLG(i)

__device__ __forceinline__ void exp_pair(float zr2  , float ph, float pl, float mult, float2& E) {
    float p = ph * mult;
    float r = (p - rintf(p)) + pl * mult;
    float ang = r * 6.283185307179586f;
    float m = ex2f(zr2 * mult);
    E.x = m * __cosf(ang);
    E.y = m * __sinf(ang);
}

__device__ __forceinline__ void prep(uint32_t S, uint32_t misc, int lane, const uint32_t* __restrict__ pv, float ldt)
{
    float dt;
    {
        float e = expf(ldt);
        uint32_t b = __float_as_uint(e);
        int low = (int)(b & 0xffffu) - 0x8000;
        if (low >= -4 && low <= 4) e = (float)exp((double)ldt);
        dt = __bfloat162float(__float2bfloat16_rn(e));
    }
    float zr[2], zi[2]; float2 cb[2];
    #pragma unroll
    for (int k = 0; k < 2; k++) {
        float are = k ? bf_hi(pv[0]) : bf_lo(pv[0]);
        float aim = k ? bf_hi(pv[1]) : bf_lo(pv[1]);
        float bre = k ? bf_hi(pv[2]) : bf_lo(pv[2]);
        float bim = k ? bf_hi(pv[3]) : bf_lo(pv[3]);
        float cre = k ? bf_hi(pv[4]) : bf_lo(pv[4]);
        float cim = k ? bf_hi(pv[5]) : bf_lo(pv[5]);
        zr[k] = dt * are; zi[k] = dt * aim;
        float dbr = dt * bre, dbi = dt * bim;
        cb[k].x = fmaf(cre, dbr, -cim * dbi);
        cb[k].y = fmaf(cre, dbi, cim * dbr);
    }
    float gmax = fmaxf(fmaxf(zr[0], zr[1]), 0.f);
    float cmax = fmaxf(fmaxf(fabsf(cb[0].x), fabsf(cb[0].y)), fmaxf(fabsf(cb[1].x), fabsf(cb[1].y)));
    gmax = __uint_as_float(__reduce_max_sync(0xffffffffu, __float_as_uint(gmax)));
    int ex = (int)(__reduce_max_sync(0xffffffffu, __float_as_uint(cmax)) >> 23);
    ex = min(max(ex, 30), 230);
    const float sc = __uint_as_float((uint32_t)(127 + 10 + 127 - ex) << 23);
    const float isc = __uint_as_float((uint32_t)(ex - 10) << 23);
    if (lane == 0) sts64f(misc, isc, gmax);

    float2 E1[2], E256[2];
    #pragma unroll
    for (int k = 0; k < 2; k++) {
        const float C1 = 0.15915494309189535f;
        const float C2 = (float)(0.15915494309189533576888 - (double)0.15915494309189535f);
        float ph = zi[k] * C1;
        float pl = fmaf(zi[k], C1, -ph) + zi[k] * C2;
        float z2 = (zr[k] - gmax) * 1.4426950408889634f;
        exp_pair(z2, ph, pl, 1.f, E1[k]);
        exp_pair(z2, ph, pl, 256.f, E256[k]);
    }
    const uint32_t wr = S + lane * 4;
    auto put = [&](int row, const H2C& v) {
        const uint32_t a = (wr ^ ((row & 7) << 4)) + row * 256;
        sts32(a, h2u(v.r)); sts32(a + 128, h2u(v.i));
    };
    float2 a[2];
    H2C h1 = hpack(E1[0], E1[1]);
    a[0] = csq(E1[0]); a[1] = csq(E1[1]); H2C h2 = hpack(a[0], a[1]);
    a[0] = csq(a[0]); a[1] = csq(a[1]); H2C h4 = hpack(a[0], a[1]);
    { H2C h0; h0.r = u2h(0x3c003c00u); h0.i = u2h(0u); put(0, h0); }
    put(1, h1); put(2, h2); put(4, h4);
    H2C h3 = hc_mul(h1, h2); put(3, h3);
    put(5, hc_mul(h4, h1));
    H2C h6 = hc_mul(h4, h2); put(6, h6);
    put(7, hc_mul(h4, h3));
    a[0] = csq(a[0]); a[1] = csq(a[1]); H2C h8 = hpack(a[0], a[1]);
    a[0] = csq(a[0]); a[1] = csq(a[1]); H2C h16 = hpack(a[0], a[1]);
    a[0] = csq(a[0]); a[1] = csq(a[1]); H2C h32 = hpack(a[0], a[1]);
    a[0] = csq(a[0]); a[1] = csq(a[1]); H2C h64 = hpack(a[0], a[1]);
    a[0] = csq(a[0]); a[1] = csq(a[1]); H2C h128 = hpack(a[0], a[1]);
    sts128(S + KS_FAC + lane * 16, h2u(h64.r), h2u(h64.i), h2u(h128.r), h2u(h128.i));
    {
        float2 c0 = make_float2(cb[0].x * sc, -cb[0].y * sc), c1 = make_float2(cb[1].x * sc, -cb[1].y * sc);
        H2C s0 = hpack(c0, c1);
        H2C s1 = hc_mulc(s0, h8), s2 = hc_mulc(s0, h16), s4 = hc_mulc(s0, h32);
        H2C s3 = hc_mulc(s1, h16);
        put(KG_SEED + 0, s0); put(KG_SEED + 1, s1); put(KG_SEED + 2, s2); put(KG_SEED + 3, s3); put(KG_SEED + 4, s4);
        put(KG_SEED + 5, hc_mulc(s1, h32)); put(KG_SEED + 6, hc_mulc(s2, h32)); put(KG_SEED + 7, hc_mulc(s3, h32));
    }
    H2C h256 = hpack(E256[0], E256[1]);
    put(8, h256); put(9, hc_mul(h256, h2)); put(10, hc_mul(h256, h4)); put(11, hc_mul(h256, h6));
    a[0] = csq(E256[0]); a[1] = csq(E256[1]); H2C h512 = hpack(a[0], a[1]);
    H2C h768 = hc_mul(h512, h256);
    put(12, h512); put(13, hc_mul(h512, h4)); put(14, h768); put(15, hc_mul(h768, h4));
    a[0] = csq(a[0]); a[1] = csq(a[1]); H2C h1024 = hpack(a[0], a[1]);
    put(16, h1024); put(17, hc_mul(h1024, h256)); put(18, hc_mul(h1024, h512)); put(19, hc_mul(h1024, h768));
    a[0] = csq(a[0]); a[1] = csq(a[1]); put(20, hpack(a[0], a[1]));
}

__device__ __forceinline__ void kmma(uint32_t KS, uint32_t misc, int lane)
{
    const int g = lane >> 2, q = lane & 3;
    float acc[2][2][3][4];
    #pragma unroll
    for (int h = 0; h < 2; h++)
        #pragma unroll
        for (int i = 0; i < 2; i++)
            #pragma unroll
            for (int j = 0; j < 3; j++)
                #pragma unroll
                for (int k = 0; k < 4; k++) acc[h][i][j][k] = 0.f;
    {
        const int mi = lane >> 3, r = lane & 7;
        const int row2 = (mi >> 1) ? (KG_SEED + r) : min(16 + r, 20);
        const uint32_t aA = KS + ((mi >> 1) * 8 + r) * 256 + (mi & 1) * 128 + (r << 4);
        const uint32_t aB = KS + row2 * 256 + (mi & 1) * 128 + ((row2 & 7) << 4);
        const uint32_t aF = KS + KS_FAC + q * 16;
        #pragma unroll
        for (int h = 0; h < 2; h++) {
            #pragma unroll
            for (int ks = 0; ks < 8; ks++) {
                uint32_t b00, b01, b10, b11, b20, b21, sr, si;
                ldsm4(b00, b01, b10, b11, (aA ^ (ks << 4)) + h * KS_HALF);
                ldsm4(b20, b21, sr, si, (aB ^ (ks << 4)) + h * KS_HALF);
                uint4 f0 = lds128(aF + ks * 64 + h * KS_HALF);
                H2C s; s.r = u2h(sr); s.i = u2h(si);
                H2C f64; f64.r = u2h(f0.x); f64.i = u2h(f0.y);
                H2C f128; f128.r = u2h(f0.z); f128.i = u2h(f0.w);
                H2C t1 = hc_mulc(s, f64), t2 = hc_mulc(s, f128);
                H2C t3 = hc_mulc(t1, f128);
                mma_f16(acc[h][0][0], sr, h2u(t1.r), si, h2u(t1.i), b00, b01);
                mma_f16(acc[h][0][1], sr, h2u(t1.r), si, h2u(t1.i), b10, b11);
                mma_f16(acc[h][0][2], sr, h2u(t1.r), si, h2u(t1.i), b20, b21);
                mma_f16(acc[h][1][0], h2u(t2.r), h2u(t3.r), h2u(t2.i), h2u(t3.i), b00, b01);
                mma_f16(acc[h][1][1], h2u(t2.r), h2u(t3.r), h2u(t2.i), h2u(t3.i), b10, b11);
                mma_f16(acc[h][1][2], h2u(t2.r), h2u(t3.r), h2u(t2.i), h2u(t3.i), b20, b21);
            }
        }
    }
    const float2 m0 = lds64f(misc), m1 = lds64f(misc + 8);
    float v[4][3][2];
    if (fmaxf(m0.y, m1.y) > 0.f) {
        #pragma unroll
        for (int idx = 0; idx < 4; idx++)
            #pragma unroll
            for (int j = 0; j < 3; j++)
                #pragma unroll
                for (int b = 0; b < 2; b++) {
                    const int gp = g + 8 * idx, c = 2 * q + b;
                    int l;
                    if (j == 0) l = 8 * gp + c;
                    else if (j == 1) l = (c < 4) ? 256 + 8 * gp + 2 * c : (c < 6 ? 512 + 8 * gp + 4 * (c - 4) : 768 + 8 * gp + 4 * (c - 6));
                    else l = 1024 + 256 * min(c, 4) + 8 * gp;
                    v[idx][j][b] = acc[0][idx >> 1][j][2 * (idx & 1) + b] * m0.x * expf(m0.y * (float)l)
                                 + acc[1][idx >> 1][j][2 * (idx & 1) + b] * m1.x * expf(m1.y * (float)l);
                }
    } else {
        #pragma unroll
        for (int idx = 0; idx < 4; idx++)
            #pragma unroll
            for (int j = 0; j < 3; j++)
                #pragma unroll
                for (int b = 0; b < 2; b++)
                    v[idx][j][b] = fmaf(acc[0][idx >> 1][j][2 * (idx & 1) + b], m0.x, acc[1][idx >> 1][j][2 * (idx & 1) + b] * m1.x);
    }
    __syncwarp();
    #pragma unroll
    for (int i = 0; i < 9; i++) sts128(KS + lane * 16 + i * 512, 0u, 0u, 0u, 0u);
    __syncwarp();
    auto tput = [&](int word, int dw, float val) {
        const uint16_t b = cvt_bf16(val);
        sts16(KS + word * 4, b); sts16(KS + (word + dw) * 4 + 2, b);
    };
    const float k512 = __shfl_sync(0xffffffffu, v[0][1][0], 2);
    #pragma unroll
    for (int idx = 0; idx < 5; idx++) {
        float pres = (idx < 4) ? v[idx][0][1] : 0.f;
        if (lane == 31) pres = (idx > 0) ? v[idx - 1][0][1] : 0.f;
        const float fop = __shfl_sync(0xffffffffu, pres, (lane + 31) & 31);
        if (idx < 4) {
            const int n = lane + 32 * idx;
            const float fe = v[idx][0][0], fo = v[idx][0][1];
            tput(TE + n, 1, fe); tput(TQ + n, 1, fop - fe); tput(TR + n, 1, fo - fe);
        } else if (lane == 0) {
            tput(TQ + 128, 1, fop - v[0][1][0]);
        }
    }
    #pragma unroll
    for (int idx = 0; idx < 4; idx++) {
        const int gp = g + 8 * idx;
        float A = v[idx][1][0], B = v[idx][1][1];
        if (idx == 3 && lane == 29) B -= k512;
        float pres = A;
        if (lane == 0) pres = (idx < 3) ? v[idx + 1 < 4 ? idx + 1 : 3][1][0] : 0.f;
        const int src = (q == 0) ? lane + 1 : ((lane + 3) & 31);
        const float an = __shfl_sync(0xffffffffu, pres, src);
        const int wa = (q < 2) ? (TE + 128 + 4 * gp + 2 * q) : (T2E + 32 * (q - 2) + gp);
        const int wb = (q < 2) ? (wa + 1) : (T2O + 32 * (q - 2) + gp);
        tput(wa, 1, A); tput(wb, 1, B);
        if (q < 2) {
            const int a = 64 + 2 * gp + q;
            const float cq = A - B, cr = an - B;
            tput(CQ + a, 1, cq); tput(CR + a, 1, cr);
            if (idx == 0 && g < 4) { tput(TQ + 2 * a + 1, 1, cq); tput(TR + 2 * a + 1, 1, cr); }
            if (lane != 0 || idx != 0) tput(T3 + 64 * q + gp, 2, v[idx][2][0]);
            tput(T3 + 64 * q + 32 + gp, 2, v[idx][2][1]);
        }
    }
    if (lane == 2) { tput(T3 + 128, 2, v[0][2][0]); sts32f(KS + (TSC + 1) * 4, k512); }
    if (lane == 0) sts16(KS + TSC * 4, cvt_bf16(v[0][2][0]));
}

template <int E0, int NE>
__device__ __forceinline__ void hconv(uint32_t U, uint32_t KS, int lane, float (&aP)[NE][4], float (&aQ)[NE][4], float (&aR)[NE][4])
{
    const int g = lane >> 2, q = lane & 3;
    const uint32_t ub = U + (lane >> 4) * U_ARR + U_Z + (lane & 7) * 272 + ((lane >> 3) & 1) * 16;
    const uint32_t fb = KS + (g - 2 * q) * 4;
    const uint32_t cb = KS + (3 + ((g + 1) >> 1) - 2 * q) * 4;
    const uint32_t meta = (g & 1) ? 0x88888888u : 0xDDDDDDDDu;
    #pragma unroll
    for (int e = 0; e < NE; e++)
        #pragma unroll
        for (int k = 0; k < 4; k++) { aP[e][k] = 0.f; aQ[e][k] = 0.f; aR[e][k] = 0.f; }
    constexpr int NB = NE + 16;
    uint32_t xe[NB][2], xo[NB][2], xs[NB][2];
    auto ldtile = [&](int b) {
        const int i = b - (E0 - 16);
        const int off = 32 * b + 16 * (b >= 0 ? b / 8 : -((7 - b) / 8));
        ldsm4(xe[i][0], xe[i][1], xo[i][0], xo[i][1], ub + off);
        xs[i][0] = badd2(xe[i][0], xo[i][0]); xs[i][1] = badd2(xe[i][1], xo[i][1]);
    };
    #pragma unroll
    for (int e = 1; e < NE; e++) ldtile(E0 + e);
    uint32_t fprev = 0, qprev = 0, rprev = 0;
    #pragma unroll
    for (int m = 0; m <= 16; m++) {
        ldtile(E0 - m);
        const uint32_t f0 = lds32(fb + (TE + 16 * m) * 4);
        const uint32_t f1 = (m < 16) ? lds32(fb + (TE + 16 * m + 8) * 4) : 0u;
        if (m <= 8) {
            const uint32_t q0 = lds32(fb + (TQ + 16 * m) * 4), q1 = lds32(fb + (TQ + 16 * m + 8) * 4);
            const uint32_t r0 = lds32(fb + (TR + 16 * m) * 4), r1 = lds32(fb + (TR + 16 * m + 8) * 4);
            #pragma unroll
            for (int e = 0; e < NE; e++) { const int i = e - m + 16; mma_bf16(aP[e], f0, f1, fprev, f0, xs[i][0], xs[i][1]); }
            #pragma unroll
            for (int e = 0; e < NE; e++) { const int i = e - m + 16; mma_bf16(aQ[e], q0, q1, qprev, q0, xo[i][0], xo[i][1]); }
            #pragma unroll
            for (int e = 0; e < NE; e++) { const int i = e - m + 16; mma_bf16(aR[e], r0, r1, rprev, r0, xe[i][0], xe[i][1]); }
            qprev = q1; rprev = r1;
        } else {
            #pragma unroll
            for (int e = 0; e < NE; e++) { const int i = e - m + 16; mma_bf16(aP[e], f0, f1, fprev, f0, xs[i][0], xs[i][1]); }
            if ((m & 1) == 0) {
                const int mp = m - 1;
                uint32_t G[4], H[4];
                #pragma unroll
                for (int k = 0; k < 4; k++) {
                    G[k] = lds32(cb + (CQ + 4 * (2 * mp - 1 + k)) * 4);
                    H[k] = lds32(cb + (CR + 4 * (2 * mp - 1 + k)) * 4);
                }
                #pragma unroll
                for (int e = 0; e < NE; e++) { const int i = e - m + 16; mma_sp(aQ[e], G[2], G[3], G[0], G[1], xo[i][0], xo[i][1], xo[i + 1][0], xo[i + 1][1], meta); }
                #pragma unroll
                for (int e = 0; e < NE; e++) { const int i = e - m + 16; mma_sp(aR[e], H[2], H[3], H[0], H[1], xe[i][0], xe[i][1], xe[i + 1][0], xe[i + 1][1], meta); }
            }
        }
        fprev = f1;
    }
}

template <int E0, int NE>
__device__ __forceinline__ void hfinal(uint32_t U, uint32_t KS, uint32_t ST, int lane, float (&aP)[NE][4], float (&aQ)[NE][4], float (&aR)[NE][4])
{
    const int g = lane >> 2, q = lane & 3;
    const uint32_t pb = KS + P2_OFF + (132 * (2 * q - 2) + g) * 4;
    const uint32_t sb = ST + (132 * 2 * q + g) * 4;
    #pragma unroll
    for (int e = 0; e < NE; e++) {
        #pragma unroll
        for (int k = 0; k < 4; k++) {
            const int w = 132 * (k & 1) + 16 * (E0 + e) + 8 * (k >> 1);
            float y0 = aP[e][k] + aQ[e][k], y1 = aP[e][k] + aR[e][k];
            if (q > 0) { y0 += lds32f(pb + w * 4); y1 += lds32f(pb + w * 4 + P2_PLANE); }
            if (E0 + e == 7 && k == 3) {
                if (lane == 28) {
                    const float k512 = lds32f(KS + (TSC + 1) * 4);
                    const float u0 = bf_lo(lds32(U + U_Z)), u1 = bf_lo(lds32(U + U_ARR + U_Z));
                    y0 = fmaf(k512, u0, y0); y1 = fmaf(k512, u0 + u1, y1);
                }
            }
            sts32(sb + w * 4, pack_bf16(y0, y1));
        }
    }
}

__device__ __forceinline__ void s23(uint32_t W, uint32_t KS, int lane)
{
    const int g = lane >> 2, q = lane & 3;
    float acc[12][4];
    #pragma unroll
    for (int i = 0; i < 12; i++)
        #pragma unroll
        for (int k = 0; k < 4; k++) acc[i][k] = 0.f;
    const int mi = lane >> 3, r = lane & 7;
    const int k16 = lane & 15;
    {
        uint32_t fe[11], fo[11];
        const uint32_t fb = KS + (g - 2 * q) * 4;
        #pragma unroll
        for (int j = -1; j <= 9; j++) { fe[j + 1] = lds32(fb + (T2E + 8 * j) * 4); fo[j + 1] = lds32(fb + (T2O + 8 * j) * 4); }
        const uint32_t xb = W + ((mi >> 1) ? X3_OFF : X5_OFF) + (k16 & 1) * XH5 + ((k16 >> 1) + 1) * 16;
        {
            uint32_t b0, b1;
            ldsm2t(b0, b1, W + X5_OFF + (k16 == 15 ? XH5 : 0));
            #pragma unroll
            for (int d = 1; d <= 4; d++) mma_bf16(acc[d - 1], fe[2 * d + 1], fe[2 * d + 2], fe[2 * d], fe[2 * d + 1], b0, b1);
        }
        #pragma unroll
        for (int kap = 0; kap < 12; kap++) {
            uint32_t e0, e1, o0, o1;
            ldsm4t(e0, e1, o0, o1, xb + kap * 128);
            #pragma unroll
            for (int d = 0; d <= 4; d++) if (kap + d < 12) mma_bf16(acc[kap + d], fe[2 * d + 1], fe[2 * d + 2], fe[2 * d], fe[2 * d + 1], e0, e1);
            #pragma unroll
            for (int d = 0; d <= 4; d++) if (kap + d < 12) mma_bf16(acc[kap + d], fo[2 * d + 1], fo[2 * d + 2], fo[2 * d], fo[2 * d + 1], o0, o1);
        }
    }
    {
        uint32_t G9[18], G7[18];
        const uint32_t g9 = KS + (T3 + 2 * ((g + 1) >> 1) - 4 * q) * 4, g7 = KS + (T3 + 2 * (g >> 1) - 4 * q + 1) * 4;
        G9[0] = G9[1] = G7[0] = G7[1] = 0u;
        #pragma unroll
        for (int j = 0; j < 16; j++) { G9[j + 2] = lds32(g9 + 32 * j); G7[j + 2] = lds32(g7 + 32 * j); }
        const uint32_t m9 = (g & 1) ? 0x88888888u : 0xDDDDDDDDu, m7 = (g & 1) ? 0xDDDDDDDDu : 0x88888888u;
        const uint32_t xb = W + X9_OFF + (lane & 1) * XH9 + (lane >> 1) * 16;
        #pragma unroll
        for (int kp = 0; kp < 4; kp++) {
            uint32_t b[4], c[4];
            ldsm4t(b[0], b[1], b[2], b[3], xb + kp * 256);
            ldsm4t(c[0], c[1], c[2], c[3], xb + (X7_OFF - X9_OFF) + kp * 256);
            #pragma unroll
            for (int rp = 2 * kp; rp < 8; rp++) {
                const int D = rp - 2 * kp;
                mma_sp(acc[rp + 4], G9[2 * D + 2], G9[2 * D + 3], G9[2 * D], G9[2 * D + 1], b[0], b[1], b[2], b[3], m9);
            }
            #pragma unroll
            for (int rp = 2 * kp; rp < 8; rp++) {
                const int D = rp - 2 * kp;
                mma_sp(acc[rp + 4], G7[2 * D + 2], G7[2 * D + 3], G7[2 * D], G7[2 * D + 1], c[0], c[1], c[2], c[3], m7);
            }
        }
    }
    {
        const uint32_t kk = lds32(KS + TSC * 4);
        const uint32_t ad = (g == 2 * q) ? kk : ((g == 2 * q + 1) ? (kk << 16) : 0u);
        const uint32_t xb = W + XV_OFF + (k16 & 1) * XH9 + ((k16 >> 1) + 1) * 16;
        #pragma unroll
        for (int rho = 3; rho < 12; rho++) {
            uint32_t b0, b1;
            ldsm2t(b0, b1, rho == 3 ? (W + XV_OFF + (k16 == 15 ? XH9 : 0)) : (xb + (rho - 4) * 128));
            mma_bf16(acc[rho], ad, 0u, 0u, ad, b0, b1);
        }
    }
    const uint32_t pb = KS + P2_OFF + (q >> 1) * P2_PLANE + (4 * g + 2 * (q & 1)) * 4;
    #pragma unroll
    for (int rho = 0; rho < 12; rho++) {
        sts64f(pb + (64 * rho + 4 * (rho >> 1)) * 4, acc[rho][0], acc[rho][1]);
        sts64f(pb + (64 * rho + 32 + 4 * (rho >> 1)) * 4, acc[rho][2], acc[rho][3]);
    }
}

template <bool FULL>
__device__ __forceinline__ void wgen_pass(uint32_t U, uint32_t W, int lam, int lane)
{
    const uint32_t a0 = U + U_Z + 16 * lam + 16 * (lam >> 4);
    const uint32_t aL = a0 - 8 - ((lane & 15) == 0 ? 16 : 0), aR = a0 + 16 + ((lane & 15) == 15 ? 16 : 0);
    uint32_t e[7], o[7];
    { uint2 t = lds64(aL); e[0] = t.x; e[1] = t.y; }
    { uint4 t = lds128(a0); e[2] = t.x; e[3] = t.y; e[4] = t.z; e[5] = t.w; }
    e[6] = lds32(aR);
    { uint2 t = lds64(aL + U_ARR); o[0] = t.x; o[1] = t.y; }
    { uint4 t = lds128(a0 + U_ARR); o[2] = t.x; o[3] = t.y; o[4] = t.z; o[5] = t.w; }
    o[6] = lds32(aR + U_ARR);
    uint32_t sA[7], sB[6], eB[6], oB[5];
    #pragma unroll
    for (int w = 1; w < 7; w++) sA[w] = badd2(e[w], o[w]);
    #pragma unroll
    for (int w = 1; w < 6; w++) { sB[w] = shift1(sA[w], sA[w + 1]); eB[w] = shift1(e[w], e[w + 1]); }
    #pragma unroll
    for (int w = 0; w < 5; w++) oB[w] = shift1(o[w], o[w + 1]);
    uint32_t x5e[4], x5o[4], x3e[4], x3o[4], x7e[4], x7o[4], x9e[4], x9o[4], xve[4];
    #pragma unroll
    for (int k = 0; k < 4; k++) {
        const int w = k + 2;
        const uint32_t d1 = badd2(sB[w - 1], sA[w]), d2 = badd2(sA[w], sB[w]);
        x5e[k] = badd2(d1, eB[w]); x5o[k] = badd2(oB[w - 1], d2);
        x3e[k] = badd2(oB[w - 2], sA[w - 1]); x3o[k] = badd2(sA[w - 1], eB[w - 1]);
        if (FULL) {
            const uint32_t t3 = badd2(d1, sB[w]);
            x7e[k] = badd2(o[w - 1], t3); x7o[k] = badd2(t3, e[w + 1]);
            x9e[k] = badd2(sA[w - 1], x7o[k]); x9o[k] = badd2(x7e[k], sA[w + 1]);
            xve[k] = badd2(sA[w - 1], x5e[k]);
        }
    }
    const uint32_t w5 = W + (lam + 1) * 16;
    sts128(w5 + X5_OFF, x5e[0], x5e[1], x5o[0], x5o[1]); sts128(w5 + X5_OFF + XH5, x5e[2], x5e[3], x5o[2], x5o[3]);
    sts128(w5 + X3_OFF, x3e[0], x3e[1], x3o[0], x3o[1]); sts128(w5 + X3_OFF + XH5, x3e[2], x3e[3], x3o[2], x3o[3]);
    if (FULL) {
        sts128(w5 + XV_OFF, xve[0], xve[1], x7e[0], x7e[1]); sts128(w5 + XV_OFF + XH9, xve[2], xve[3], x7e[2], x7e[3]);
        sts128(w5 - 16 + X9_OFF + XH9, x9e[0], x9e[1], x9o[0], x9o[1]);
        sts128(w5 - 16 + X7_OFF + XH9, x7e[0], x7e[1], x7o[0], x7o[1]);
        if (lam < 63) {
            sts128(w5 + X9_OFF, x9e[2], x9e[3], x9o[2], x9o[3]);
            sts128(w5 + X7_OFF, x7e[2], x7e[3], x7o[2], x7o[3]);
        }
    }
}

__device__ __forceinline__ void wgen(uint32_t U, uint32_t W, int lane)
{
    wgen_pass<true>(U, W, lane, lane);
    wgen_pass<true>(U, W, lane + 32, lane);
    wgen_pass<false>(U, W, lane + 64, lane);
    if (lane == 0) {
        const uint32_t e0 = lds32(U + U_Z), o0 = lds32(U + U_Z + U_ARR);
        const uint32_t s0 = badd2(e0, o0);
        const uint32_t a = e0 << 16, b = s0 << 16;
        const uint32_t c = badd2(b, __byte_perm(s0, e0, 0x7610));
        const uint32_t d = badd2(b, s0);
        sts128(W + X5_OFF + XH5, 0u, a, 0u, b);
        sts128(W + XV_OFF + XH9, 0u, a, 0u, b);
        sts128(W + X9_OFF, 0u, __byte_perm(e0, c, 0x7610), 0u, d);
        sts128(W + X7_OFF, 0u, b, 0u, __byte_perm(e0, c, 0x7610));
        sts128(W + X5_OFF, 0u, 0u, 0u, 0u);
        sts128(W + XV_OFF, 0u, 0u, 0u, 0u);
    }
}

template <int CL, int GCH>
__global__ void __launch_bounds__(64 * (GCH / CL), 1)
ssm_kernel(const __nv_bfloat16* __restrict__ u, const __nv_bfloat16* __restrict__ A_re, const __nv_bfloat16* __restrict__ A_im,
           const __nv_bfloat16* __restrict__ B_re, const __nv_bfloat16* __restrict__ B_im, const __nv_bfloat16* __restrict__ C_re,
           const __nv_bfloat16* __restrict__ C_im, const __nv_bfloat16* __restrict__ log_dt, const __nv_bfloat16* __restrict__ Dsk,
           __nv_bfloat16* __restrict__ out)
{
    constexpr int NS = GCH / CL, RPC = L_ / CL, NCG = GCH / 32;
    constexpr int YP = RPC * 2 + 16;
    constexpr int YIN_OFF = NS * SLOT;
    constexpr int MB_OFF = YIN_OFF + GCH * YP + (GCH / 8) * 32;
    constexpr int MB_U = MB_OFF, MB_Y = MB_OFF + 8, MISC = MB_OFF + 16;
    extern __shared__ __align__(128) unsigned char smem[];
    const uint32_t sb = smem_u32(smem);
    const int tid = threadIdx.x, lane = tid & 31, w = tid >> 5;
    uint32_t rank; asm("mov.u32 %0, %%cluster_ctarank;" : "=r"(rank));
    const int chbase = (blockIdx.x / CL) * GCH;
    const int slot = (w < NS) ? w : w - NS, h = (w < NS) ? 0 : 1;
    const int ch = chbase + rank + CL * slot;

    TLG(15); TL(0);
    uint32_t pv[6]; float ldt;
    {
        const int o = ch * N_ + 64 * h + 2 * lane;
        pv[0] = __ldg(reinterpret_cast<const uint32_t*>(A_re + o));
        pv[1] = __ldg(reinterpret_cast<const uint32_t*>(A_im + o));
        pv[2] = __ldg(reinterpret_cast<const uint32_t*>(B_re + o));
        pv[3] = __ldg(reinterpret_cast<const uint32_t*>(B_im + o));
        pv[4] = __ldg(reinterpret_cast<const uint32_t*>(C_re + o));
        pv[5] = __ldg(reinterpret_cast<const uint32_t*>(C_im + o));
        ldt = __bfloat162float(log_dt[ch]);
    }
    const int c4 = tid & 7, xx = tid >> 3, cg = xx % NCG, combo = xx / NCG, unit = combo >> 1, par = combo & 1;
    uint2 ur[8];
    {
        const uint2* p = reinterpret_cast<const uint2*>(u + (size_t)(RPC * rank + 16 * unit + par) * D_ + chbase + 32 * cg + 4 * c4);
        #pragma unroll
        for (int r = 0; r < 8; r++) ur[r] = __ldg(p + r * (2 * D_ / 4));
    }
    if (tid == 0) {
        mbar_init(sb + MB_U, 1);
        mbar_init(sb + MB_Y, 1);
        asm volatile("fence.mbarrier_init.release.cluster;" ::: "memory");
        mbar_arrive_tx(sb + MB_U, NS * 4096);
        mbar_arrive_tx(sb + MB_Y, GCH * RPC * 2);
    }
    asm volatile("barrier.cluster.arrive.relaxed.aligned;" ::: "memory");
    const uint32_t U = sb + slot * SLOT, W = U + W_OFF, KS = U + KS_OFF;
    for (int i = lane; i < U_Z / 16; i += 32) sts128(U + h * U_ARR + i * 16, 0u, 0u, 0u, 0u);
    __syncthreads();
    asm volatile("barrier.cluster.wait.acquire.aligned;" ::: "memory");
    TL(1);
    {
        const int j0 = (RPC / 2) * rank + 8 * unit;
        const uint32_t off = par * U_ARR + U_Z + 2 * j0 + 16 * (j0 >> 7);
        #pragma unroll
        for (int i = 0; i < 4; i++) {
            const uint32_t sel = (i & 1) ? 0x7632 : 0x5410;
            const uint32_t* a = reinterpret_cast<const uint32_t*>(&ur[0]);
            const uint32_t o0 = __byte_perm(a[0 + (i >> 1)], a[2 + (i >> 1)], sel);
            const uint32_t o1 = __byte_perm(a[4 + (i >> 1)], a[6 + (i >> 1)], sel);
            const uint32_t o2 = __byte_perm(a[8 + (i >> 1)], a[10 + (i >> 1)], sel);
            const uint32_t o3 = __byte_perm(a[12 + (i >> 1)], a[14 + (i >> 1)], sel);
            const int c = 32 * cg + 4 * c4 + i;
            const uint32_t dr = c % CL, ds = c / CL;
            const uint32_t dst = mapa(sb + ds * SLOT + off, dr), mb = mapa(sb + MB_U, dr);
            asm volatile("st.async.weak.shared::cluster.mbarrier::complete_tx::bytes.v4.b32 [%0], {%1,%2,%3,%4}, [%5];"
                         ::"r"(dst), "r"(o0), "r"(o1), "r"(o2), "r"(o3), "r"(mb) : "memory");
        }
    }
    TL(2);
    prep(KS + h * KS_HALF, sb + MISC + slot * 16 + h * 8, lane, pv, ldt);
    TL(3);
    const int idA = 1 + 2 * slot, idB = 2 + 2 * slot;
    const uint32_t ST = W;
    if (h == 0) {
        nb_sync(idA);
        TL(4);
        kmma(KS, sb + MISC + slot * 16, lane);
        nb_arrive(idB);
        TL(5);
        mbar_wait(sb + MB_U, 0);
        float aP[4][4], aQ[4][4], aR[4][4];
        hconv<0, 4>(U, KS, lane, aP, aQ, aR);
        TL(6);
        nb_sync(idA);
        TL(7);
        hfinal<0, 4>(U, KS, ST, lane, aP, aQ, aR);
    } else {
        nb_arrive(idA);
        mbar_wait(sb + MB_U, 0);
        TL(4);
        wgen(U, W, lane);
        TL(5);
        nb_sync(idB);
        TL(6);
        s23(W, KS, lane);
        nb_arrive(idA);
        TL(7);
        float aP[4][4], aQ[4][4], aR[4][4];
        hconv<4, 4>(U, KS, lane, aP, aQ, aR);
        hfinal<4, 4>(U, KS, ST, lane, aP, aQ, aR);
    }
    TL(8);
    asm volatile("fence.proxy.async.shared::cta;" ::: "memory");
    __syncwarp();
    if (lane < 8) {
        const int blk = 2 * lane + h;
        const uint32_t dr = blk * CL / 16;
        const int c = rank + CL * slot;
        const uint32_t dst = mapa(sb + YIN_OFF + c * YP + (c >> 3) * 32 + ((blk * 128) % RPC) * 2, dr);
        const uint32_t mb = mapa(sb + MB_Y, dr);
        asm volatile("cp.async.bulk.shared::cluster.shared::cta.mbarrier::complete_tx::bytes [%0], [%1], %2, [%3];"
                     ::"r"(dst), "r"(ST + (132 * lane + 64 * h) * 4), "r"(256), "r"(mb) : "memory");
    }
    {
        const int g = lane >> 2, q = lane & 3;
        uint4 us[4]; uint4 dv[4];
        #pragma unroll
        for (int i = 0; i < 4; i++) {
            const int un = w * 4 + i, ocg = un % NCG, rg = un / NCG;
            const size_t o = (size_t)(RPC * rank + 8 * rg + g) * D_ + chbase + 32 * ocg + 8 * q;
            us[i] = __ldg(reinterpret_cast<const uint4*>(u + o));
            dv[i] = __ldg(reinterpret_cast<const uint4*>(Dsk + chbase + 32 * ocg + 8 * q));
        }
        TL(9);
        mbar_wait(sb + MB_Y, 0);
        asm volatile("barrier.cluster.arrive.relaxed.aligned;" ::: "memory");
        TL(10);
        const int mj = lane >> 3, mi = lane & 7;
        const int cl = 8 * (mi >> 1) + 2 * mj + (mi & 1);
        #pragma unroll
        for (int i = 0; i < 4; i++) {
            const int un = w * 4 + i, ocg = un % NCG, rg = un / NCG;
            const int c = 32 * ocg + cl;
            uint32_t y0, y1, y2, y3;
            ldsm4t(y0, y1, y2, y3, sb + YIN_OFF + c * YP + (c >> 3) * 32 + rg * 16);
            uint4 o;
            o.x = badd2(y0, bmul2(us[i].x, dv[i].x)); o.y = badd2(y1, bmul2(us[i].y, dv[i].y));
            o.z = badd2(y2, bmul2(us[i].z, dv[i].z)); o.w = badd2(y3, bmul2(us[i].w, dv[i].w));
            *reinterpret_cast<uint4*>(out + (size_t)(RPC * rank + 8 * rg + g) * D_ + chbase + 32 * ocg + 8 * q) = o;
        }
    }
    TL(11);
    asm volatile("barrier.cluster.wait.acquire.aligned;" ::: "memory");
    TL(12); TLG(14);
}

template <int CL, int GCH>
struct Cfg {
    static constexpr int NS = GCH / CL, RPC = L_ / CL, YP = RPC * 2 + 16;
    static constexpr int SMEM = NS * SLOT + GCH * YP + (GCH / 8) * 32 + 16 + NS * 16 + 48;
    static constexpr int NT = 64 * NS, GRID = (D_ / GCH) * CL;
};

template <int CL, int GCH>
static bool setup_cfg(cudaLaunchConfig_t& cfg, cudaLaunchAttribute* at, bool check)
{
    using C = Cfg<CL, GCH>;
    if (cudaFuncSetAttribute(ssm_kernel<CL, GCH>, cudaFuncAttributeMaxDynamicSharedMemorySize, C::SMEM) != cudaSuccess) { cudaGetLastError(); return false; }
    if (CL > 8 && cudaFuncSetAttribute(ssm_kernel<CL, GCH>, cudaFuncAttributeNonPortableClusterSizeAllowed, 1) != cudaSuccess) { cudaGetLastError(); return false; }
    cfg = cudaLaunchConfig_t{};
    cfg.gridDim = dim3(C::GRID); cfg.blockDim = dim3(C::NT); cfg.dynamicSmemBytes = C::SMEM; cfg.stream = cudaStreamPerThread;
    at[0].id = cudaLaunchAttributeClusterDimension;
    at[0].val.clusterDim.x = CL; at[0].val.clusterDim.y = 1; at[0].val.clusterDim.z = 1;
    cfg.attrs = at; cfg.numAttrs = 1;
    if (check) {
        int nc = 0;
        if (cudaOccupancyMaxActiveClusters(&nc, ssm_kernel<CL, GCH>, &cfg) != cudaSuccess) { cudaGetLastError(); return false; }
        if (nc < D_ / GCH) return false;
    }
    return true;
}

}

extern "C" void kernel_launch(void* const* d_in, const int* in_sizes, int n_in, void* d_out, int out_size)
{
    static int mode = -1;
    static cudaLaunchConfig_t cfg;
    static cudaLaunchAttribute at[1];
    if (mode < 0) {
        if (setup_cfg<16, 96>(cfg, at, true)) mode = 0;
        else { setup_cfg<8, 32>(cfg, at, false); mode = 1; }
    }
    const __nv_bfloat16* p[9];
    for (int i = 0; i < 9; i++) p[i] = (const __nv_bfloat16*)d_in[i];
    if (mode == 0)
        cudaLaunchKernelEx(&cfg, ssm_kernel<16, 96>, p[0], p[1], p[2], p[3], p[4], p[5], p[6], p[7], p[8], (__nv_bfloat16*)d_out);
    else
        cudaLaunchKernelEx(&cfg, ssm_kernel<8, 32>, p[0], p[1], p[2], p[3], p[4], p[5], p[6], p[7], p[8], (__nv_bfloat16*)d_out);
}
```

```cpp
#include <cuda_runtime.h>
#include <cuda_bf16.h>
#include <cuda_fp16.h>
#include <stdint.h>

namespace {

constexpr int L_ = 2048, D_ = 576, N_ = 128;

constexpr int U_Z = 544, U_ARR = 2720, U_SIZE = 5504;
constexpr int W_OFF = U_SIZE;
constexpr int X5_OFF = 0, XH5 = 1600, X3_OFF = 3200, X9_OFF = 6400, XH9 = 1088, X7_OFF = 8512, XV_OFF = 10624, W_SIZE = 12800;
constexpr int KS_OFF = W_OFF + W_SIZE;
constexpr int KS_SIZE = 15872;
constexpr int SLOT = KS_OFF + KS_SIZE;
constexpr int KG_SEED = 21, KG_FAC = 37 * 256;
constexpr int T4E = 0;
constexpr int T4Q = 4352;
constexpr int T4R = 6912;
constexpr int PQ = 9472;
constexpr int PR = 10048;
constexpr int XW = 10624;
constexpr int XK = 12192;
constexpr int P2E = 13136;
constexpr int P2O = 13840;
constexpr int PT3 = 14544;
constexpr int TSC = 15856;
constexpr int P2_OFF = 0, P2_PLANE = 816 * 4, ST_OFF = 2 * P2_PLANE;
constexpr int NEK = 6;

__device__ __forceinline__ uint32_t smem_u32(const void* p) { return (uint32_t)__cvta_generic_to_shared(p); }
__device__ __forceinline__ uint32_t mapa(uint32_t addr, uint32_t rank) {
    uint32_t r; asm volatile("mapa.shared::cluster.u32 %0, %1, %2;" : "=r"(r) : "r"(addr), "r"(rank)); return r;
}
__device__ __forceinline__ void mbar_init(uint32_t bar, uint32_t cnt) {
    asm volatile("mbarrier.init.shared::cta.b64 [%0], %1;" ::"r"(bar), "r"(cnt) : "memory");
}
__device__ __forceinline__ void mbar_arrive_tx(uint32_t bar, uint32_t bytes) {
    asm volatile("mbarrier.arrive.expect_tx.shared::cta.b64 _, [%0], %1;" ::"r"(bar), "r"(bytes) : "memory");
}
__device__ __forceinline__ void mbar_wait(uint32_t bar, uint32_t parity) {
    uint32_t ok; int it = 0;
    do {
        asm volatile("{\n.reg .pred p;\nmbarrier.try_wait.parity.shared::cta.b64 p, [%1], %2;\nselp.u32 %0, 1, 0, p;\n}"
                     : "=r"(ok) : "r"(bar), "r"(parity) : "memory");
        if (++it > (1 << 22)) __trap();
    } while (!ok);
}
__device__ __forceinline__ void nb_sync(int id) { asm volatile("bar.sync %0, 64;" ::"r"(id) : "memory"); }
__device__ __forceinline__ void nb_arrive(int id) { asm volatile("bar.arrive %0, 64;" ::"r"(id) : "memory"); }
__device__ __forceinline__ void ldsm4(uint32_t& r0, uint32_t& r1, uint32_t& r2, uint32_t& r3, uint32_t a) {
    asm volatile("ldmatrix.sync.aligned.m8n8.x4.shared.b16 {%0,%1,%2,%3}, [%4];" : "=r"(r0), "=r"(r1), "=r"(r2), "=r"(r3) : "r"(a) : "memory");
}
__device__ __forceinline__ void ldsm4t(uint32_t& r0, uint32_t& r1, uint32_t& r2, uint32_t& r3, uint32_t a) {
    asm volatile("ldmatrix.sync.aligned.m8n8.x4.trans.shared.b16 {%0,%1,%2,%3}, [%4];" : "=r"(r0), "=r"(r1), "=r"(r2), "=r"(r3) : "r"(a) : "memory");
}
__device__ __forceinline__ void ldsm2t(uint32_t& r0, uint32_t& r1, uint32_t a) {
    asm volatile("ldmatrix.sync.aligned.m8n8.x2.trans.shared.b16 {%0,%1}, [%2];" : "=r"(r0), "=r"(r1) : "r"(a) : "memory");
}
__device__ __forceinline__ void mma_bf16(float* c, uint32_t a0, uint32_t a1, uint32_t a2, uint32_t a3, uint32_t b0, uint32_t b1) {
    asm volatile("mma.sync.aligned.m16n8k16.row.col.f32.bf16.bf16.f32 {%0,%1,%2,%3},{%4,%5,%6,%7},{%8,%9},{%0,%1,%2,%3};"
                 : "+f"(c[0]), "+f"(c[1]), "+f"(c[2]), "+f"(c[3]) : "r"(a0), "r"(a1), "r"(a2), "r"(a3), "r"(b0), "r"(b1));
}
__device__ __forceinline__ void mma_sp(float* c, uint32_t a0, uint32_t a1, uint32_t a2, uint32_t a3, uint32_t b0, uint32_t b1, uint32_t b2, uint32_t b3, uint32_t e) {
    asm volatile("mma.sp::ordered_metadata.sync.aligned.m16n8k32.row.col.f32.bf16.bf16.f32 {%0,%1,%2,%3},{%4,%5,%6,%7},{%8,%9,%10,%11},{%0,%1,%2,%3},%12,0x0;"
                 : "+f"(c[0]), "+f"(c[1]), "+f"(c[2]), "+f"(c[3]) : "r"(a0), "r"(a1), "r"(a2), "r"(a3), "r"(b0), "r"(b1), "r"(b2), "r"(b3), "r"(e));
}
__device__ __forceinline__ void mma_f16(float* c, uint32_t a0, uint32_t a1, uint32_t a2, uint32_t a3, uint32_t b0, uint32_t b1) {
    asm volatile("mma.sync.aligned.m16n8k16.row.col.f32.f16.f16.f32 {%0,%1,%2,%3},{%4,%5,%6,%7},{%8,%9},{%0,%1,%2,%3};"
                 : "+f"(c[0]), "+f"(c[1]), "+f"(c[2]), "+f"(c[3]) : "r"(a0), "r"(a1), "r"(a2), "r"(a3), "r"(b0), "r"(b1));
}
__device__ __forceinline__ uint32_t lds32(uint32_t a) { uint32_t v; asm volatile("ld.shared.u32 %0, [%1];" : "=r"(v) : "r"(a) : "memory"); return v; }
__device__ __forceinline__ float lds32f(uint32_t a) { float v; asm volatile("ld.shared.f32 %0, [%1];" : "=f"(v) : "r"(a) : "memory"); return v; }
__device__ __forceinline__ float2 lds64f(uint32_t a) { float2 v; asm volatile("ld.shared.v2.f32 {%0,%1}, [%2];" : "=f"(v.x), "=f"(v.y) : "r"(a) : "memory"); return v; }
__device__ __forceinline__ uint2 lds64(uint32_t a) { uint2 v; asm volatile("ld.shared.v2.u32 {%0,%1}, [%2];" : "=r"(v.x), "=r"(v.y) : "r"(a) : "memory"); return v; }
__device__ __forceinline__ uint4 lds128(uint32_t a) { uint4 v; asm volatile("ld.shared.v4.u32 {%0,%1,%2,%3}, [%4];" : "=r"(v.x), "=r"(v.y), "=r"(v.z), "=r"(v.w) : "r"(a) : "memory"); return v; }
__device__ __forceinline__ void sts16(uint32_t a, uint16_t v) { asm volatile("st.shared.u16 [%0], %1;" ::"r"(a), "h"(v) : "memory"); }
__device__ __forceinline__ void sts32(uint32_t a, uint32_t v) { asm volatile("st.shared.u32 [%0], %1;" ::"r"(a), "r"(v) : "memory"); }
__device__ __forceinline__ void sts32f(uint32_t a, float v) { asm volatile("st.shared.f32 [%0], %1;" ::"r"(a), "f"(v) : "memory"); }
__device__ __forceinline__ void sts64(uint32_t a, uint32_t x, uint32_t y) { asm volatile("st.shared.v2.u32 [%0], {%1,%2};" ::"r"(a), "r"(x), "r"(y) : "memory"); }
__device__ __forceinline__ void sts64f(uint32_t a, float x, float y) { asm volatile("st.shared.v2.f32 [%0], {%1,%2};" ::"r"(a), "f"(x), "f"(y) : "memory"); }
__device__ __forceinline__ void sts128(uint32_t a, uint32_t x, uint32_t y, uint32_t z, uint32_t w) { asm volatile("st.shared.v4.u32 [%0], {%1,%2,%3,%4};" ::"r"(a), "r"(x), "r"(y), "r"(z), "r"(w) : "memory"); }

__device__ __forceinline__ uint32_t pack_bf16(float lo, float hi) {
    uint32_t r; asm("cvt.rn.bf16x2.f32 %0, %1, %2;" : "=r"(r) : "f"(hi), "f"(lo)); return r;
}
__device__ __forceinline__ uint16_t cvt_bf16(float v) { uint16_t r; asm("cvt.rn.bf16.f32 %0, %1;" : "=h"(r) : "f"(v)); return r; }
__device__ __forceinline__ uint32_t pack_f16(float lo, float hi) {
    uint32_t r; asm("cvt.rn.f16x2.f32 %0, %1, %2;" : "=r"(r) : "f"(hi), "f"(lo)); return r;
}
__device__ __forceinline__ uint32_t badd2(uint32_t a, uint32_t b) {
    __nv_bfloat162 r = __hadd2_rn(*reinterpret_cast<__nv_bfloat162*>(&a), *reinterpret_cast<__nv_bfloat162*>(&b));
    return *reinterpret_cast<uint32_t*>(&r);
}
__device__ __forceinline__ uint32_t bmul2(uint32_t a, uint32_t b) {
    __nv_bfloat162 r = __hmul2_rn(*reinterpret_cast<__nv_bfloat162*>(&a), *reinterpret_cast<__nv_bfloat162*>(&b));
    return *reinterpret_cast<uint32_t*>(&r);
}
__device__ __forceinline__ uint32_t shift1(uint32_t a, uint32_t b) { return __byte_perm(a, b, 0x5432); }

__device__ __forceinline__ float shf(float v, int src) { return __shfl_sync(0xffffffffu, v, src); }
__device__ __forceinline__ uint32_t shu(uint32_t v, int src) { return __shfl_sync(0xffffffffu, v, src); }
__device__ __forceinline__ void stsm4t(uint32_t a, uint32_t r0, uint32_t r1, uint32_t r2, uint32_t r3) {
    asm volatile("stmatrix.sync.aligned.m8n8.x4.trans.shared.b16 [%0], {%1,%2,%3,%4};" ::"r"(a), "r"(r0), "r"(r1), "r"(r2), "r"(r3) : "memory");
}
__device__ __forceinline__ void bulk_s2c(uint32_t dst, uint32_t src, uint32_t bytes, uint32_t mb) {
    asm volatile("cp.async.bulk.shared::cluster.shared::cta.mbarrier::complete_tx::bytes [%0], [%1], %2, [%3];"
                 ::"r"(dst), "r"(src), "r"(bytes), "r"(mb) : "memory");
}
__device__ __forceinline__ void cl_arrive() { asm volatile("barrier.cluster.arrive.relaxed.aligned;" ::: "memory"); }
__device__ __forceinline__ void cl_wait() { asm volatile("barrier.cluster.wait.acquire.aligned;" ::: "memory"); }

struct H2C { __half2 r, i; };
__device__ __forceinline__ H2C hc_mul(const H2C& a, const H2C& b) {
    H2C o;
    o.r = __hfma2(a.r, b.r, __hneg2(__hmul2(a.i, b.i)));
    o.i = __hfma2(a.r, b.i, __hmul2(a.i, b.r));
    return o;
}
__device__ __forceinline__ H2C hc_mulc(const H2C& a, const H2C& e) {
    H2C o;
    o.r = __hfma2(a.r, e.r, __hmul2(a.i, e.i));
    o.i = __hfma2(a.i, e.r, __hneg2(__hmul2(a.r, e.i)));
    return o;
}
__device__ __forceinline__ uint32_t h2u(__half2 h) { return *reinterpret_cast<uint32_t*>(&h); }
__device__ __forceinline__ __half2 u2h(uint32_t u) { return *reinterpret_cast<__half2*>(&u); }
__device__ __forceinline__ float2 csq(float2 a) { return make_float2(fmaf(a.x, a.x, -a.y * a.y), (a.x + a.x) * a.y); }
__device__ __forceinline__ H2C hpack(float2 a, float2 b) { H2C o; o.r = u2h(pack_f16(a.x, b.x)); o.i = u2h(pack_f16(a.y, b.y)); return o; }
__device__ __forceinline__ float ex2f(float x) { float r; asm("ex2.approx.ftz.f32 %0, %1;" : "=f"(r) : "f"(x)); return r; }
__device__ __forceinline__ float bf_lo(uint32_t v) { return __uint_as_float(v << 16); }
__device__ __forceinline__ float bf_hi(uint32_t v) { return __uint_as_float(v & 0xffff0000u); }

#define TL(i)
#define TLG(i)

__device__ __forceinline__ void exp_pair(float zr2  , float ph, float pl, float mult, float2& E) {
    float p = ph * mult;
    float r = (p - rintf(p)) + pl * mult;
    float ang = r * 6.283185307179586f;
    float m = ex2f(zr2 * mult);
    E.x = m * __cosf(ang);
    E.y = m * __sinf(ang);
}

__device__ __forceinline__ void prep(uint32_t S, int lane, const uint32_t* __restrict__ pv, uint32_t ldtb, float& isc, float& gmaxo)
{
    float dt;
    {
        const float ldt = __uint_as_float(ldtb << 16);
        float e = expf(ldt);
        uint32_t b = __float_as_uint(e);
        int low = (int)(b & 0xffffu) - 0x8000;
        if (low >= -4 && low <= 4) e = (float)exp((double)ldt);
        dt = __bfloat162float(__float2bfloat16_rn(e));
    }
    float zr[2], zi[2]; float2 cb[2];
    #pragma unroll
    for (int k = 0; k < 2; k++) {
        float are = k ? bf_hi(pv[0]) : bf_lo(pv[0]);
        float aim = k ? bf_hi(pv[1]) : bf_lo(pv[1]);
        float bre = k ? bf_hi(pv[2]) : bf_lo(pv[2]);
        float bim = k ? bf_hi(pv[3]) : bf_lo(pv[3]);
        float cre = k ? bf_hi(pv[4]) : bf_lo(pv[4]);
        float cim = k ? bf_hi(pv[5]) : bf_lo(pv[5]);
        zr[k] = dt * are; zi[k] = dt * aim;
        float dbr = dt * bre, dbi = dt * bim;
        cb[k].x = fmaf(cre, dbr, -cim * dbi);
        cb[k].y = fmaf(cre, dbi, cim * dbr);
    }
    float gmax = fmaxf(fmaxf(zr[0], zr[1]), 0.f);
    float cmax = fmaxf(fmaxf(fabsf(cb[0].x), fabsf(cb[0].y)), fmaxf(fabsf(cb[1].x), fabsf(cb[1].y)));
    gmax = __uint_as_float(__reduce_max_sync(0xffffffffu, __float_as_uint(gmax)));
    int ex = (int)(__reduce_max_sync(0xffffffffu, __float_as_uint(cmax)) >> 23);
    ex = min(max(ex, 30), 230);
    const float sc = __uint_as_float((uint32_t)(127 + 10 + 127 - ex) << 23);
    isc = __uint_as_float((uint32_t)(ex - 10) << 23);
    gmaxo = gmax;

    float2 E1[2], E256[2];
    #pragma unroll
    for (int k = 0; k < 2; k++) {
        const float C1 = 0.15915494309189535f;
        const float C2 = (float)(0.15915494309189533576888 - (double)0.15915494309189535f);
        float ph = zi[k] * C1;
        float pl = fmaf(zi[k], C1, -ph) + zi[k] * C2;
        float z2 = (zr[k] - gmax) * 1.4426950408889634f;
        exp_pair(z2, ph, pl, 1.f, E1[k]);
        exp_pair(z2, ph, pl, 256.f, E256[k]);
    }
    const uint32_t wr = S + lane * 4;
    auto put = [&](int row, const H2C& v) {
        const uint32_t a = (wr ^ ((row & 7) << 4)) + row * 256;
        sts32(a, h2u(v.r)); sts32(a + 128, h2u(v.i));
    };
    float2 a[2];
    H2C h1 = hpack(E1[0], E1[1]);
    a[0] = csq(E1[0]); a[1] = csq(E1[1]); H2C h2 = hpack(a[0], a[1]);
    a[0] = csq(a[0]); a[1] = csq(a[1]); H2C h4 = hpack(a[0], a[1]);
    a[0] = csq(a[0]); a[1] = csq(a[1]); H2C h8 = hpack(a[0], a[1]);
    a[0] = csq(a[0]); a[1] = csq(a[1]); H2C h16 = hpack(a[0], a[1]);
    a[0] = csq(a[0]); a[1] = csq(a[1]); H2C h32 = hpack(a[0], a[1]);
    a[0] = csq(a[0]); a[1] = csq(a[1]); H2C h64 = hpack(a[0], a[1]);
    a[0] = csq(a[0]); a[1] = csq(a[1]); H2C h128 = hpack(a[0], a[1]);
    {
        float2 c0 = make_float2(cb[0].x * sc, -cb[0].y * sc), c1 = make_float2(cb[1].x * sc, -cb[1].y * sc);
        H2C s[4];
        s[0] = hpack(c0, c1);
        s[1] = hc_mulc(s[0], h8); s[2] = hc_mulc(s[0], h16); s[3] = hc_mulc(s[1], h16);
        #pragma unroll
        for (int k = 0; k < 4; k++) {
            const int row = KG_SEED + (k & 1) + 8 * (k >> 1);
            H2C t1 = hc_mulc(s[k], h64), t2 = hc_mulc(s[k], h128);
            put(row, s[k]); put(row + 2, t1); put(row + 4, t2); put(row + 6, hc_mulc(t1, h128));
        }
    }
    sts64(S + KG_FAC + lane * 8, h2u(h32.r), h2u(h32.i));
    { H2C h0; h0.r = u2h(0x3c003c00u); h0.i = u2h(0u); put(0, h0); }
    put(1, h1); put(2, h2); put(4, h4);
    H2C h3 = hc_mul(h1, h2); put(3, h3);
    put(5, hc_mul(h4, h1));
    H2C h6 = hc_mul(h4, h2); put(6, h6);
    put(7, hc_mul(h4, h3));
    H2C h256 = hpack(E256[0], E256[1]);
    put(8, h256); put(10, hc_mul(h256, h2)); put(12, hc_mul(h256, h4)); put(14, hc_mul(h256, h6));
    a[0] = csq(E256[0]); a[1] = csq(E256[1]); H2C h512 = hpack(a[0], a[1]);
    H2C h768 = hc_mul(h512, h256);
    put(9, h512); put(11, hc_mul(h512, h4)); put(13, h768); put(15, hc_mul(h768, h4));
    a[0] = csq(a[0]); a[1] = csq(a[1]); H2C h1024 = hpack(a[0], a[1]);
    put(16, h1024); put(17, hc_mul(h1024, h256)); put(18, hc_mul(h1024, h512)); put(19, hc_mul(h1024, h768));
    a[0] = csq(a[0]); a[1] = csq(a[1]); put(20, hpack(a[0], a[1]));
}

__device__ __forceinline__ void kmma(uint32_t S, int lane, float isc, float gmax, float (&acc)[2][3][4])
{
    const int q = lane & 3;
    #pragma unroll
    for (int i = 0; i < 2; i++)
        #pragma unroll
        for (int j = 0; j < 3; j++)
            #pragma unroll
            for (int k = 0; k < 4; k++) acc[i][j][k] = 0.f;
    const int mi = lane >> 3, r = lane & 7;
    const int rowA = KG_SEED + (mi & 1) * 8 + r;
    const int row2 = (r == 1) ? 20 : 16 + (r >> 1);
    const uint32_t aA = S + rowA * 256 + (mi >> 1) * 128 + ((rowA & 7) << 4);
    const uint32_t aB = S + ((mi >> 1) * 8 + r) * 256 + (mi & 1) * 128 + (r << 4);
    const uint32_t aC = (S + row2 * 256 + (mi & 1) * 128 + ((row2 & 7) << 4)) ^ ((mi >> 1) << 4);
    const uint32_t aF = S + KG_FAC + q * 8;
    #pragma unroll
    for (int ks = 0; ks < 8; ks += 2) {
        uint32_t c[4];
        ldsm4(c[0], c[1], c[2], c[3], aC ^ (ks << 4));
        #pragma unroll
        for (int k2 = 0; k2 < 2; k2++) {
            uint32_t a0, a1, a2, a3, b00, b01, b10, b11;
            ldsm4(a0, a1, a2, a3, aA ^ ((ks + k2) << 4));
            ldsm4(b00, b01, b10, b11, aB ^ ((ks + k2) << 4));
            const uint2 f0 = lds64(aF + (ks + k2) * 32);
            H2C f; f.r = u2h(f0.x); f.i = u2h(f0.y);
            H2C s0; s0.r = u2h(a0); s0.i = u2h(a2);
            H2C s1; s1.r = u2h(a1); s1.i = u2h(a3);
            const H2C t0 = hc_mulc(s0, f), t1 = hc_mulc(s1, f);
            mma_f16(acc[0][0], a0, a1, a2, a3, b00, b01);
            mma_f16(acc[0][1], a0, a1, a2, a3, b10, b11);
            mma_f16(acc[0][2], a0, a1, a2, a3, c[2 * k2], c[2 * k2 + 1]);
            mma_f16(acc[1][0], h2u(t0.r), h2u(t1.r), h2u(t0.i), h2u(t1.i), b00, b01);
            mma_f16(acc[1][1], h2u(t0.r), h2u(t1.r), h2u(t0.i), h2u(t1.i), b10, b11);
            mma_f16(acc[1][2], h2u(t0.r), h2u(t1.r), h2u(t0.i), h2u(t1.i), c[2 * k2], c[2 * k2 + 1]);
        }
    }
    if (gmax > 0.f) {
        const float g2 = gmax * 1.4426950408889634f;
        const int seed0 = 64 * (lane >> 3) + 8 * ((lane >> 2) & 1);
        #pragma unroll
        for (int i = 0; i < 2; i++)
            #pragma unroll
            for (int t = 0; t < 3; t++)
                #pragma unroll
                for (int k = 0; k < 4; k++) {
                    const int b = k & 1;
                    int l = seed0 + 16 * ((k >> 1) + 2 * i);
                    if (t == 0) l += 2 * q + b;
                    else if (t == 1) l += b ? (512 + 256 * (q >> 1) + 4 * (q & 1)) : (256 + 2 * q);
                    else l += b ? 2048 : (1024 + 256 * q);
                    acc[i][t][k] *= isc * exp2f(g2 * (float)l);
                }
    } else {
        #pragma unroll
        for (int i = 0; i < 2; i++)
            #pragma unroll
            for (int t = 0; t < 3; t++)
                #pragma unroll
                for (int k = 0; k < 4; k++) acc[i][t][k] *= isc;
    }
}

__device__ __forceinline__ void ktables(uint32_t KS, int lane, const float (&fe)[4], const float (&fo)[4], float (&fu)[4], float k512)
{
    const int a = lane >> 3, r = lane & 7;
    const bool r7 = (r == 7), l31 = (lane == 31);
    const int sp = (r > 0) ? lane - 1 : lane + 7;
    const int s0 = (lane + 31) & 31;
    {
        const uint32_t z = KS + (lane & 15) * 16;
        sts128((lane < 16) ? z + T4E : z + T4E + 256 * 16, 0u, 0u, 0u, 0u);
        sts128((lane < 16) ? z + T4Q : z + T4R, 0u, 0u, 0u, 0u);
        sts128(KS + PQ + lane * 16, 0u, 0u, 0u, 0u); sts128(KS + PQ + 512 + lane * 16, 0u, 0u, 0u, 0u);
        if (lane < 8) sts128(KS + PQ + 1024 + lane * 16, 0u, 0u, 0u, 0u);
    }
    if (l31) fu[3] -= k512;
    auto pred = [&](const float (&x)[4], float wrapv, float (&o)[4]) {
        o[0] = shf(r7 ? (l31 ? wrapv : x[3]) : x[0], s0);
        #pragma unroll
        for (int j = 1; j < 4; j++) o[j] = shf(r7 ? x[j - 1] : x[j], sp);
    };
    float A[4], B[4], C[4], Pu[4];
    pred(fe, 0.f, A); pred(fo, 0.f, B); pred(fu, fe[3], Pu); pred(B, 0.f, C);
    uint32_t We[4], Wq[4], Wr[4], Wu[4];
    float d[4];
    #pragma unroll
    for (int j = 0; j < 4; j++) {
        We[j] = pack_bf16(fe[j], A[j]);
        Wr[j] = pack_bf16(fo[j] - fe[j], B[j] - A[j]);
        Wq[j] = pack_bf16(B[j] - fe[j], C[j] - A[j]);
        Wu[j] = pack_bf16(fu[j], Pu[j]);
        d[j] = fu[j] - Pu[j];
    }
    uint32_t Xq[2], Xr[2];
    {
        const uint32_t D01 = pack_bf16(d[0], d[1]), D12 = pack_bf16(d[1], d[2]);
        const uint32_t Dp = shu(r7 ? (D01 << 16) : D01, sp);
        const uint32_t Dn = shu((r == 0) ? D12 : D01, (r < 7) ? lane + 1 : lane - 7);
        const bool odd = r & 1;
        const uint32_t sq = (odd ? D01 : Dp) ^ 0x80008000u, sr = odd ? Dn : D01;
        Xq[0] = odd ? (sq & 0xffffu) : (sq << 16); Xq[1] = odd ? (sq >> 16) : (sq & 0xffff0000u);
        Xr[0] = odd ? (sr & 0xffffu) : (sr << 16); Xr[1] = odd ? (sr >> 16) : (sr & 0xffff0000u);
        const float q128 = shf(fo[3], 31) - shf(fu[0], 0);
        const uint32_t q128b = cvt_bf16(q128);
        const uint32_t w3q = shu(Wq[3], 31), w3r = shu(Wr[3], 31);
        if (lane == 0) { Xq[0] = __byte_perm(q128b, w3q, 0x5410); Xr[0] = w3r << 16; }
        if (lane == 1) Xq[0] |= q128b << 16;
    }
    __syncwarp();
    uint32_t ad[4];
    #pragma unroll
    for (int s = 0; s < 4; s++) {
        const int dd = (s + a) & 3;
        ad[s] = KS + (32 * a + r + 8) * 16 + dd * 4 + (dd == 1 ? -128 : (dd == 2 ? 128 : 0));
    }
    #pragma unroll
    for (int j = 0; j < 4; j++)
        #pragma unroll
        for (int s = 0; s < 4; s++) {
            sts32(ad[s] + T4E + 128 * j, We[j]);
            sts32(ad[s] + T4Q + 128 * j, Wq[j]);
            sts32(ad[s] + T4R + 128 * j, Wr[j]);
            sts32(ad[s] + T4E + 2048 + 128 * j, Wu[j]);
        }
    if (a == 0) {
        #pragma unroll
        for (int j = 0; j < 2; j++)
            #pragma unroll
            for (int s = 0; s < 4; s++) { sts32(ad[s] + T4Q + 2048 + 128 * j, Xq[j]); sts32(ad[s] + T4R + 2048 + 128 * j, Xr[j]); }
    }
    if (l31) {
        const uint16_t b = (uint16_t)(Wu[3] & 0xffffu);
        sts16(KS + T4E + 264 * 16 + 2, b); sts16(KS + T4E + 264 * 16 + 14, b); sts16(KS + T4E + 256 * 16 + 6, b);
        const uint16_t nb = b ^ 0x8000u;
        const uint32_t p = KS + PR + (127 - 60) * 8;
        sts16(p, nb); sts16(p - 28, nb); sts16(p + 10, nb); sts16(p - 18, nb);
    }
    {
        const uint32_t p = KS + ((r & 1) ? PQ : PR) + (4 + 16 * a + ((r - 1) >> 1)) * 8;
        const float sg = (r & 1) ? -1.f : 1.f;
        #pragma unroll
        for (int j = 0; j < 4; j++) {
            const uint16_t b = cvt_bf16(d[j] * sg);
            if (j > 0 || lane != 0) { sts16(p + 32 * j, b); sts16(p + 32 * j - 28, b); sts16(p + 32 * j + 10, b); sts16(p + 32 * j - 18, b); }
        }
    }
}

__device__ __forceinline__ void wtables(uint32_t KS, int lane, const float (&v2)[4], const float (&v3)[4], float k2048)
{
    const int a = lane >> 3, e = (lane >> 2) & 1, q = lane & 3;
    #pragma unroll
    for (int i = 0; i < 6; i++) if (i < 5 || lane < 11) sts128(KS + P2E + (lane + 32 * i) * 16, 0u, 0u, 0u, 0u);
    __syncwarp();
    {
        const uint32_t p = KS + ((q & 1) ? P2O : P2E) + (16 + 32 * (q >> 1) + 8 * a + e) * 8;
        #pragma unroll
        for (int j = 0; j < 4; j++) {
            const uint16_t b = cvt_bf16(v2[j]);
            sts16(p + 16 * j, b); sts16(p + 16 * j - 60, b); sts16(p + 16 * j + 10, b); sts16(p + 16 * j - 50, b);
        }
    }
    {
        const uint32_t p = KS + PT3 + (32 + 32 * q + 8 * a + e) * 8;
        #pragma unroll
        for (int j = 0; j < 4; j++) {
            const uint16_t b = cvt_bf16(v3[j]);
            if (j > 0 || lane != 0) { sts16(p + 16 * j, b); sts16(p + 16 * j - 60, b); sts16(p + 16 * j + 18, b); sts16(p + 16 * j - 42, b); }
        }
    }
    if (lane == 0) {
        const uint16_t b = cvt_bf16(k2048);
        const uint32_t p = KS + PT3 + (32 + 128) * 8;
        sts16(p, b); sts16(p - 60, b); sts16(p + 18, b); sts16(p - 42, b);
        sts64(KS + TSC, (uint32_t)cvt_bf16(v3[0]), __float_as_uint(v2[0]));
    }
}

__host__ __device__ constexpr int tile_off(int b) { return 32 * b + 16 * (b >= 0 ? b / 8 : -((7 - b) / 8)); }

template <int E0, int NE>
__device__ __forceinline__ void hconv(uint32_t U, uint32_t KS, int lane, float (&aP)[NE][4], float (&aQ)[NE][4], float (&aR)[NE][4])
{
    const int g = lane >> 2, q = lane & 3;
    const uint32_t rowb = U + U_Z + (lane & 7) * 272;
    const uint32_t ub = rowb + (lane >> 4) * U_ARR + ((lane >> 3) & 1) * 16;
    const uint32_t uq = rowb + (lane >> 3) * 16, uq2 = uq + (lane >> 4) * 16;
    const uint32_t tb = KS + (g - 2 * q + 8) * 16;
    const uint32_t pb = KS + (((g + 1) >> 1) - 2 * q - 69 + 80) * 8;
    const uint32_t meta = (g & 1) ? 0x88888888u : 0xDDDDDDDDu;
    #pragma unroll
    for (int e = 0; e < NE; e++)
        #pragma unroll
        for (int k = 0; k < 4; k++) { aP[e][k] = 0.f; aQ[e][k] = 0.f; aR[e][k] = 0.f; }
    constexpr int B0 = E0 - 16;
    uint32_t xe[NE + 16][2], xo[NE + 16][2], xs[NE + 16][2];
    uint32_t qo[NE + 6][4], qe[NE + 6][4];
    auto ldtile = [&](int b) {
        const int i = b - B0;
        ldsm4(xe[i][0], xe[i][1], xo[i][0], xo[i][1], ub + tile_off(b));
        xs[i][0] = badd2(xe[i][0], xo[i][0]); xs[i][1] = badd2(xe[i][1], xo[i][1]);
    };
    auto ldquad = [&](int b) {
        const int i = b - B0;
        const uint32_t ad = ((tile_off(b + 1) - tile_off(b) == 32) ? uq : uq2) + tile_off(b);
        ldsm4(qe[i][0], qe[i][1], qe[i][2], qe[i][3], ad);
        ldsm4(qo[i][0], qo[i][1], qo[i][2], qo[i][3], ad + U_ARR);
        if (b < E0 - 9) { xs[i][0] = badd2(qe[i][0], qo[i][0]); xs[i][1] = badd2(qe[i][1], qo[i][1]); }
    };
    uint4 fE = lds128(tb + T4E), fQ = lds128(tb + T4Q), fR = lds128(tb + T4R);
    #pragma unroll
    for (int e = 0; e < NE; e++) ldtile(E0 + e);
    #pragma unroll
    for (int m = 0; m <= 9; m++) {
        const uint4 cE = fE, cQ = fQ, cR = fR;
        fE = lds128(tb + T4E + 256 * (m + 1));
        if (m < 8) { fQ = lds128(tb + T4Q + 256 * (m + 1)); fR = lds128(tb + T4R + 256 * (m + 1)); }
        if (m < 9) ldtile(E0 - m - 1);
        else {
            #pragma unroll
            for (int b = E0 - 10; b <= E0 + NE - 11; b++) ldquad(b);
        }
        #pragma unroll
        for (int e = 0; e < NE; e++) { const int i = e - m + 16; mma_bf16(aP[e], cE.x, cE.y, cE.z, cE.w, xs[i][0], xs[i][1]); }
        if (m <= 8) {
            #pragma unroll
            for (int e = 0; e < NE; e++) { const int i = e - m + 16; mma_bf16(aQ[e], cQ.x, cQ.y, cQ.z, cQ.w, xo[i][0], xo[i][1]); }
            #pragma unroll
            for (int e = 0; e < NE; e++) { const int i = e - m + 16; mma_bf16(aR[e], cR.x, cR.y, cR.z, cR.w, xe[i][0], xe[i][1]); }
        }
    }
    #pragma unroll
    for (int m = 10; m <= 16; m++) {
        const uint4 cE = fE;
        if (m < 16) { fE = lds128(tb + T4E + 256 * (m + 1)); ldquad(E0 - m - 1); }
        if ((m & 1) == 0) {
            const uint2 g1 = lds64(pb + PQ + (8 * m - 80 + 8) * 8), g0 = lds64(pb + PQ + (8 * m - 80) * 8);
            const uint2 h1 = lds64(pb + PR + (8 * m - 80 + 8) * 8), h0 = lds64(pb + PR + (8 * m - 80) * 8);
            #pragma unroll
            for (int e = 0; e < NE; e++) { const int i = e - m + 16; mma_bf16(aP[e], cE.x, cE.y, cE.z, cE.w, xs[i][0], xs[i][1]); }
            #pragma unroll
            for (int e = 0; e < NE; e++) { const int i = e - m + 16; mma_sp(aQ[e], g1.x, g1.y, g0.x, g0.y, qo[i][0], qo[i][1], qo[i][2], qo[i][3], meta); }
            #pragma unroll
            for (int e = 0; e < NE; e++) { const int i = e - m + 16; mma_sp(aR[e], h1.x, h1.y, h0.x, h0.y, qe[i][0], qe[i][1], qe[i][2], qe[i][3], meta); }
        } else {
            #pragma unroll
            for (int e = 0; e < NE; e++) { const int i = e - m + 16; mma_bf16(aP[e], cE.x, cE.y, cE.z, cE.w, xs[i][0], xs[i][1]); }
        }
    }
}

template <int E0, int NE>
__device__ __forceinline__ void hfinal(uint32_t U, uint32_t KS, uint32_t W, int lane, float (&aP)[NE][4], float (&aQ)[NE][4], float (&aR)[NE][4])
{
    const int g = lane >> 2, q = lane & 3;
    const uint32_t pb = W + P2_OFF + (132 * (2 * q - 2) + g) * 4;
    const uint32_t sb = W + ST_OFF + (132 * 2 * q + g) * 4;
    #pragma unroll
    for (int e = 0; e < NE; e++) {
        #pragma unroll
        for (int k = 0; k < 4; k++) {
            const int w = 132 * (k & 1) + 16 * (E0 + e) + 8 * (k >> 1);
            float y0 = aP[e][k] + aQ[e][k], y1 = aP[e][k] + aR[e][k];
            if (q > 0) { y0 += lds32f(pb + w * 4); y1 += lds32f(pb + w * 4 + P2_PLANE); }
            if (E0 + e == 7 && k == 3) {
                if (lane == 28) {
                    const float k512 = lds32f(KS + TSC + 4);
                    const float u0 = bf_lo(lds32(U + U_Z)), u1 = bf_lo(lds32(U + U_ARR + U_Z));
                    y0 = fmaf(k512, u0, y0); y1 = fmaf(k512, u0 + u1, y1);
                }
            }
            sts32(sb + w * 4, pack_bf16(y0, y1));
        }
    }
}

__device__ __forceinline__ void s23(uint32_t W, uint32_t KS, int lane)
{
    const int g = lane >> 2, q = lane & 3;
    float acc[12][4];
    #pragma unroll
    for (int i = 0; i < 12; i++)
        #pragma unroll
        for (int k = 0; k < 4; k++) acc[i][k] = 0.f;
    const int k16 = lane & 15, mi = lane >> 3;
    {
        uint2 e1[5], e0[5], o1[5], o0[5];
        const uint32_t fb = KS + (g - 2 * q + 16) * 8;
        #pragma unroll
        for (int d = 0; d < 5; d++) {
            e1[d] = lds64(fb + P2E + 128 * d); e0[d] = lds64(fb + P2E + 128 * d - 64);
            o1[d] = lds64(fb + P2O + 128 * d); o0[d] = lds64(fb + P2O + 128 * d - 64);
        }
        const uint32_t xb = W + ((mi >> 1) ? X3_OFF : X5_OFF) + (k16 & 1) * XH5 + ((k16 >> 1) + 1) * 16;
        {
            uint32_t b0, b1;
            ldsm2t(b0, b1, W + X5_OFF + (k16 == 15 ? XH5 : 0));
            #pragma unroll
            for (int d = 1; d <= 4; d++) mma_bf16(acc[d - 1], e1[d].x, e1[d].y, e0[d].x, e0[d].y, b0, b1);
        }
        #pragma unroll
        for (int kap = 0; kap < 12; kap++) {
            uint32_t x0, x1, y0, y1;
            ldsm4t(x0, x1, y0, y1, xb + kap * 128);
            #pragma unroll
            for (int d = 0; d <= 4; d++) if (kap + d < 12) mma_bf16(acc[kap + d], e1[d].x, e1[d].y, e0[d].x, e0[d].y, x0, x1);
            #pragma unroll
            for (int d = 0; d <= 4; d++) if (kap + d < 12) mma_bf16(acc[kap + d], o1[d].x, o1[d].y, o0[d].x, o0[d].y, y0, y1);
        }
    }
    {
        uint2 G9[9], G7[9];
        const uint32_t g9 = KS + PT3 + (32 + 2 * ((g + 1) >> 1) - 4 * q) * 8, g7 = KS + PT3 + (32 + 2 * (g >> 1) - 4 * q + 1) * 8;
        const uint32_t m9 = (g & 1) ? 0x88888888u : 0xDDDDDDDDu, m7 = (g & 1) ? 0xDDDDDDDDu : 0x88888888u;
        const uint32_t xb = W + X9_OFF + (lane & 1) * XH9 + (lane >> 1) * 16;
        uint2 A9[8][2], A7[8][2];
        #pragma unroll
        for (int D = 0; D < 8; D++) {
            A9[D][0] = lds64(g9 + 128 * D); A9[D][1] = lds64(g9 + 128 * D - 128);
            A7[D][0] = lds64(g7 + 128 * D); A7[D][1] = lds64(g7 + 128 * D - 128);
        }
        (void)G9; (void)G7;
        #pragma unroll
        for (int kp = 0; kp < 4; kp++) {
            uint32_t b[4], c[4];
            ldsm4t(b[0], b[1], b[2], b[3], xb + kp * 256);
            ldsm4t(c[0], c[1], c[2], c[3], xb + (X7_OFF - X9_OFF) + kp * 256);
            #pragma unroll
            for (int rp = 2 * kp; rp < 8; rp++) {
                const int D = rp - 2 * kp;
                mma_sp(acc[rp + 4], A9[D][0].x, A9[D][0].y, A9[D][1].x, A9[D][1].y, b[0], b[1], b[2], b[3], m9);
            }
            #pragma unroll
            for (int rp = 2 * kp; rp < 8; rp++) {
                const int D = rp - 2 * kp;
                mma_sp(acc[rp + 4], A7[D][0].x, A7[D][0].y, A7[D][1].x, A7[D][1].y, c[0], c[1], c[2], c[3], m7);
            }
        }
    }
    {
        const uint32_t kk = lds32(KS + TSC);
        const uint32_t ad = (g == 2 * q) ? kk : ((g == 2 * q + 1) ? (kk << 16) : 0u);
        const uint32_t xb = W + XV_OFF + (k16 & 1) * XH9 + ((k16 >> 1) + 1) * 16;
        #pragma unroll
        for (int rho = 3; rho < 12; rho++) {
            uint32_t b0, b1;
            ldsm2t(b0, b1, rho == 3 ? (W + XV_OFF + (k16 == 15 ? XH9 : 0)) : (xb + (rho - 4) * 128));
            mma_bf16(acc[rho], ad, 0u, 0u, ad, b0, b1);
        }
    }
    __syncwarp();
    const uint32_t pb = W + P2_OFF + (q >> 1) * P2_PLANE + (4 * g + 2 * (q & 1)) * 4;
    #pragma unroll
    for (int rho = 0; rho < 12; rho++) {
        sts64f(pb + (64 * rho + 4 * (rho >> 1)) * 4, acc[rho][0], acc[rho][1]);
        sts64f(pb + (64 * rho + 32 + 4 * (rho >> 1)) * 4, acc[rho][2], acc[rho][3]);
    }
}

template <bool FULL>
__device__ __forceinline__ void wgen_pass(uint32_t U, uint32_t W, int lam, int lane)
{
    const uint32_t a0 = U + U_Z + 16 * lam + 16 * (lam >> 4);
    const uint32_t aL = a0 - 8 - ((lane & 15) == 0 ? 16 : 0), aR = a0 + 16 + ((lane & 15) == 15 ? 16 : 0);
    uint32_t e[7], o[7];
    { uint2 t = lds64(aL); e[0] = t.x; e[1] = t.y; }
    { uint4 t = lds128(a0); e[2] = t.x; e[3] = t.y; e[4] = t.z; e[5] = t.w; }
    e[6] = lds32(aR);
    { uint2 t = lds64(aL + U_ARR); o[0] = t.x; o[1] = t.y; }
    { uint4 t = lds128(a0 + U_ARR); o[2] = t.x; o[3] = t.y; o[4] = t.z; o[5] = t.w; }
    o[6] = lds32(aR + U_ARR);
    uint32_t sA[7], sB[6], eB[6], oB[5];
    #pragma unroll
    for (int w = 1; w < 7; w++) sA[w] = badd2(e[w], o[w]);
    #pragma unroll
    for (int w = 1; w < 6; w++) { sB[w] = shift1(sA[w], sA[w + 1]); eB[w] = shift1(e[w], e[w + 1]); }
    #pragma unroll
    for (int w = 0; w < 5; w++) oB[w] = shift1(o[w], o[w + 1]);
    uint32_t x5e[4], x5o[4], x3e[4], x3o[4], x7e[4], x7o[4], x9e[4], x9o[4], xve[4];
    #pragma unroll
    for (int k = 0; k < 4; k++) {
        const int w = k + 2;
        const uint32_t d1 = badd2(sB[w - 1], sA[w]), d2 = badd2(sA[w], sB[w]);
        x5e[k] = badd2(d1, eB[w]); x5o[k] = badd2(oB[w - 1], d2);
        x3e[k] = badd2(oB[w - 2], sA[w - 1]); x3o[k] = badd2(sA[w - 1], eB[w - 1]);
        if (FULL) {
            const uint32_t t3 = badd2(d1, sB[w]);
            x7e[k] = badd2(o[w - 1], t3); x7o[k] = badd2(t3, e[w + 1]);
            x9e[k] = badd2(sA[w - 1], x7o[k]); x9o[k] = badd2(x7e[k], sA[w + 1]);
            xve[k] = badd2(sA[w - 1], x5e[k]);
        }
    }
    const uint32_t w5 = W + (lam + 1) * 16;
    sts128(w5 + X5_OFF, x5e[0], x5e[1], x5o[0], x5o[1]); sts128(w5 + X5_OFF + XH5, x5e[2], x5e[3], x5o[2], x5o[3]);
    sts128(w5 + X3_OFF, x3e[0], x3e[1], x3o[0], x3o[1]); sts128(w5 + X3_OFF + XH5, x3e[2], x3e[3], x3o[2], x3o[3]);
    if (FULL) {
        sts128(w5 + XV_OFF, xve[0], xve[1], x7e[0], x7e[1]); sts128(w5 + XV_OFF + XH9, xve[2], xve[3], x7e[2], x7e[3]);
        sts128(w5 - 16 + X9_OFF + XH9, x9e[0], x9e[1], x9o[0], x9o[1]);
        sts128(w5 - 16 + X7_OFF + XH9, x7e[0], x7e[1], x7o[0], x7o[1]);
        if (lam < 63) {
            sts128(w5 + X9_OFF, x9e[2], x9e[3], x9o[2], x9o[3]);
            sts128(w5 + X7_OFF, x7e[2], x7e[3], x7o[2], x7o[3]);
        }
    }
}

__device__ __forceinline__ void wgen(uint32_t U, uint32_t W, int lane)
{
    wgen_pass<true>(U, W, lane, lane);
    wgen_pass<true>(U, W, lane + 32, lane);
    wgen_pass<false>(U, W, lane + 64, lane);
    if (lane == 0) {
        const uint32_t e0 = lds32(U + U_Z), o0 = lds32(U + U_Z + U_ARR);
        const uint32_t s0 = badd2(e0, o0);
        const uint32_t a = e0 << 16, b = s0 << 16;
        const uint32_t c = badd2(b, __byte_perm(s0, e0, 0x7610));
        const uint32_t d = badd2(b, s0);
        sts128(W + X5_OFF + XH5, 0u, a, 0u, b);
        sts128(W + XV_OFF + XH9, 0u, a, 0u, b);
        sts128(W + X9_OFF, 0u, __byte_perm(e0, c, 0x7610), 0u, d);
        sts128(W + X7_OFF, 0u, b, 0u, __byte_perm(e0, c, 0x7610));
        sts128(W + X5_OFF, 0u, 0u, 0u, 0u);
        sts128(W + XV_OFF, 0u, 0u, 0u, 0u);
    }
}

template <int CL, int GCH>
__global__ void __launch_bounds__(64 * (GCH / CL), 1)
ssm_kernel(const __nv_bfloat16* __restrict__ u, const __nv_bfloat16* __restrict__ A_re, const __nv_bfloat16* __restrict__ A_im,
           const __nv_bfloat16* __restrict__ B_re, const __nv_bfloat16* __restrict__ B_im, const __nv_bfloat16* __restrict__ C_re,
           const __nv_bfloat16* __restrict__ C_im, const __nv_bfloat16* __restrict__ log_dt, const __nv_bfloat16* __restrict__ Dsk,
           __nv_bfloat16* __restrict__ out)
{
    constexpr int NS = GCH / CL, RPC = L_ / CL, NCG = GCH / 32;
    constexpr int YP = RPC * 2 + 16;
    constexpr int YIN_OFF = NS * SLOT;
    constexpr int MB_OFF = YIN_OFF + GCH * YP + (GCH / 8) * 32;
    constexpr int MB_U = MB_OFF, MB_Y = MB_OFF + 8;
    extern __shared__ __align__(128) unsigned char smem[];
    const uint32_t sb = smem_u32(smem);
    const int tid = threadIdx.x, lane = tid & 31, w = tid >> 5;
    uint32_t rank; asm("mov.u32 %0, %%cluster_ctarank;" : "=r"(rank));
    const int chbase = (blockIdx.x / CL) * GCH;
    const int slot = (w < NS) ? w : w - NS, h = (w < NS) ? 0 : 1;
    const int ch = chbase + rank + CL * slot;
    const int g = lane >> 2, q = lane & 3;

    TLG(15); TL(0);
    uint32_t pv[6], ldtb;
    {
        const int o = ch * N_ + 64 * h + 2 * lane;
        pv[0] = __ldg(reinterpret_cast<const uint32_t*>(A_re + o));
        pv[1] = __ldg(reinterpret_cast<const uint32_t*>(A_im + o));
        pv[2] = __ldg(reinterpret_cast<const uint32_t*>(B_re + o));
        pv[3] = __ldg(reinterpret_cast<const uint32_t*>(B_im + o));
        pv[4] = __ldg(reinterpret_cast<const uint32_t*>(C_re + o));
        pv[5] = __ldg(reinterpret_cast<const uint32_t*>(C_im + o));
        ldtb = __ldg(reinterpret_cast<const unsigned short*>(log_dt + ch));
    }
    const int ucg = w % NCG, upar = (w / NCG) & 1, ublk = (w / NCG) >> 1;
    uint4 ur[4];
    {
        const uint4* p = reinterpret_cast<const uint4*>(u + (size_t)(RPC * rank + 64 * ublk + 2 * g + upar) * D_ + chbase + 32 * ucg + 8 * q);
        #pragma unroll
        for (int i = 0; i < 4; i++) ur[i] = __ldg(p + i * (16 * D_ / 8));
    }
    if (tid == 0) {
        mbar_init(sb + MB_U, 1);
        mbar_init(sb + MB_Y, 1);
        asm volatile("fence.mbarrier_init.release.cluster;" ::: "memory");
        mbar_arrive_tx(sb + MB_U, NS * 4096);
        mbar_arrive_tx(sb + MB_Y, GCH * RPC * 2);
    }
    cl_arrive();
    const uint32_t U = sb + slot * SLOT, W = U + W_OFF, KS = U + KS_OFF;
    sts128(U + h * U_ARR + lane * 16, 0u, 0u, 0u, 0u);
    if (lane < U_Z / 16 - 32) sts128(U + h * U_ARR + 512 + lane * 16, 0u, 0u, 0u, 0u);
    TL(1);
    const uint32_t S = h ? W : KS;
    float isc, gmax;
    prep(S, lane, pv, ldtb, isc, gmax);
    TL(2);
    {
        const int mj = lane >> 3, mi = lane & 7;
        const int c = 32 * ucg + 8 * (mi >> 1) + 2 * mj + (mi & 1);
        const uint32_t a = sb + YIN_OFF + c * YP + (c >> 3) * 32 + upar * RPC + ublk * 64;
        #pragma unroll
        for (int i = 0; i < 4; i++) stsm4t(a + i * 16, ur[i].x, ur[i].y, ur[i].z, ur[i].w);
        asm volatile("fence.proxy.async.shared::cta;" ::: "memory");
        cl_wait();
        __syncwarp();
        const int c2 = 32 * ucg + lane;
        const int j0 = (RPC / 2) * rank + 32 * ublk;
        const uint32_t dr = c2 % CL;
        bulk_s2c(mapa(sb + (c2 / CL) * SLOT + upar * U_ARR + U_Z + 2 * j0 + 16 * (j0 >> 7), dr),
                 sb + YIN_OFF + c2 * YP + (c2 >> 3) * 32 + upar * RPC + ublk * 64, 64, mapa(sb + MB_U, dr));
    }
    TL(3);
    float acc[2][3][4];
    kmma(S, lane, isc, gmax, acc);
    TL(4);
    const int idX = 1 + 2 * slot, idY = 2 + 2 * slot;
    if (h == 0) {
        sts128(KS + XK + lane * 16, __float_as_uint(acc[0][1][1]), __float_as_uint(acc[0][1][3]), __float_as_uint(acc[1][1][1]), __float_as_uint(acc[1][1][3]));
        sts128(KS + XK + 512 + lane * 16, __float_as_uint(acc[0][2][0]), __float_as_uint(acc[0][2][2]), __float_as_uint(acc[1][2][0]), __float_as_uint(acc[1][2][2]));
        if (lane == 0) sts32f(KS + XK + 1024, acc[0][2][1]);
        nb_sync(idX);
        const uint4 t0 = lds128(KS + XW + lane * 16), t1 = lds128(KS + XW + 512 + lane * 16), t2 = lds128(KS + XW + 1024 + lane * 16);
        const float k512 = shf(acc[0][1][1], 0) + lds32f(KS + XW + 1536);
        float fe[4], fo[4], fu[4];
        fe[0] = acc[0][0][0] + __uint_as_float(t0.x); fe[1] = acc[0][0][2] + __uint_as_float(t0.y);
        fe[2] = acc[1][0][0] + __uint_as_float(t0.z); fe[3] = acc[1][0][2] + __uint_as_float(t0.w);
        fo[0] = acc[0][0][1] + __uint_as_float(t1.x); fo[1] = acc[0][0][3] + __uint_as_float(t1.y);
        fo[2] = acc[1][0][1] + __uint_as_float(t1.z); fo[3] = acc[1][0][3] + __uint_as_float(t1.w);
        fu[0] = acc[0][1][0] + __uint_as_float(t2.x); fu[1] = acc[0][1][2] + __uint_as_float(t2.y);
        fu[2] = acc[1][1][0] + __uint_as_float(t2.z); fu[3] = acc[1][1][2] + __uint_as_float(t2.w);
        ktables(KS, lane, fe, fo, fu, k512);
        nb_arrive(idX);
        TL(5);
        mbar_wait(sb + MB_U, 0);
        cl_arrive();
        TL(6);
        float aP[NEK][4], aQ[NEK][4], aR[NEK][4];
        hconv<0, NEK>(U, KS, lane, aP, aQ, aR);
        TL(7);
        nb_sync(idY);
        hfinal<0, NEK>(U, KS, W, lane, aP, aQ, aR);
    } else {
        sts128(KS + XW + lane * 16, __float_as_uint(acc[0][0][0]), __float_as_uint(acc[0][0][2]), __float_as_uint(acc[1][0][0]), __float_as_uint(acc[1][0][2]));
        sts128(KS + XW + 512 + lane * 16, __float_as_uint(acc[0][0][1]), __float_as_uint(acc[0][0][3]), __float_as_uint(acc[1][0][1]), __float_as_uint(acc[1][0][3]));
        sts128(KS + XW + 1024 + lane * 16, __float_as_uint(acc[0][1][0]), __float_as_uint(acc[0][1][2]), __float_as_uint(acc[1][1][0]), __float_as_uint(acc[1][1][2]));
        if (lane == 0) sts32f(KS + XW + 1536, acc[0][1][1]);
        nb_sync(idX);
        const uint4 t0 = lds128(KS + XK + lane * 16), t1 = lds128(KS + XK + 512 + lane * 16);
        const float k2048 = acc[0][2][1] + lds32f(KS + XK + 1024);
        float v2[4], v3[4];
        v2[0] = acc[0][1][1] + __uint_as_float(t0.x); v2[1] = acc[0][1][3] + __uint_as_float(t0.y);
        v2[2] = acc[1][1][1] + __uint_as_float(t0.z); v2[3] = acc[1][1][3] + __uint_as_float(t0.w);
        v3[0] = acc[0][2][0] + __uint_as_float(t1.x); v3[1] = acc[0][2][2] + __uint_as_float(t1.y);
        v3[2] = acc[1][2][0] + __uint_as_float(t1.z); v3[3] = acc[1][2][2] + __uint_as_float(t1.w);
        __syncwarp();
        wtables(KS, lane, v2, v3, k2048);
        TL(5);
        mbar_wait(sb + MB_U, 0);
        cl_arrive();
        TL(6);
        wgen(U, W, lane);
        __syncwarp();
        s23(W, KS, lane);
        nb_arrive(idY);
        TL(7);
        nb_sync(idX);
        float aP[8 - NEK][4], aQ[8 - NEK][4], aR[8 - NEK][4];
        hconv<NEK, 8 - NEK>(U, KS, lane, aP, aQ, aR);
        __syncwarp();
        hfinal<NEK, 8 - NEK>(U, KS, W, lane, aP, aQ, aR);
    }
    TL(8);
    asm volatile("fence.proxy.async.shared::cta;" ::: "memory");
    cl_wait();
    __syncwarp();
    {
        const int n = h ? lane : (lane >> 1);
        const int e0 = h ? NEK : ((lane & 1) ? 4 : 0);
        const int ne = h ? (8 - NEK) : ((lane & 1) ? NEK - 4 : 4);
        if (lane < (h ? 8 : 16)) {
            const int t0 = 256 * n + 32 * e0;
            const uint32_t dr = t0 / RPC;
            const int c = rank + CL * slot;
            bulk_s2c(mapa(sb + YIN_OFF + c * YP + (c >> 3) * 32 + (t0 % RPC) * 2, dr), W + ST_OFF + (132 * n + 16 * e0) * 4, ne * 64,
                     mapa(sb + MB_Y, dr));
        }
    }
    {
        uint4 us[4]; uint4 dv[4];
        #pragma unroll
        for (int i = 0; i < 4; i++) {
            const int un = w * 4 + i, ocg = un % NCG, rg = un / NCG;
            const size_t o = (size_t)(RPC * rank + 8 * rg + g) * D_ + chbase + 32 * ocg + 8 * q;
            us[i] = __ldg(reinterpret_cast<const uint4*>(u + o));
            dv[i] = __ldg(reinterpret_cast<const uint4*>(Dsk + chbase + 32 * ocg + 8 * q));
        }
        TL(9);
        mbar_wait(sb + MB_Y, 0);
        cl_arrive();
        TL(10);
        const int mj = lane >> 3, mi = lane & 7;
        const int cl = 8 * (mi >> 1) + 2 * mj + (mi & 1);
        #pragma unroll
        for (int i = 0; i < 4; i++) {
            const int un = w * 4 + i, ocg = un % NCG, rg = un / NCG;
            const int c = 32 * ocg + cl;
            uint32_t y0, y1, y2, y3;
            ldsm4t(y0, y1, y2, y3, sb + YIN_OFF + c * YP + (c >> 3) * 32 + rg * 16);
            uint4 o;
            o.x = badd2(y0, bmul2(us[i].x, dv[i].x)); o.y = badd2(y1, bmul2(us[i].y, dv[i].y));
            o.z = badd2(y2, bmul2(us[i].z, dv[i].z)); o.w = badd2(y3, bmul2(us[i].w, dv[i].w));
            asm volatile("st.global.v4.u32 [%0], {%1,%2,%3,%4};" ::"l"(out + (size_t)(RPC * rank + 8 * rg + g) * D_ + chbase + 32 * ocg + 8 * q),
                         "r"(o.x), "r"(o.y), "r"(o.z), "r"(o.w) : "memory");
        }
    }
    TL(11);
    cl_wait();
    TL(12); TLG(14);
}

template <int CL, int GCH>
struct Cfg {
    static constexpr int NS = GCH / CL, RPC = L_ / CL, YP = RPC * 2 + 16;
    static constexpr int SMEM = NS * SLOT + GCH * YP + (GCH / 8) * 32 + 64;
    static constexpr int NT = 64 * NS, GRID = (D_ / GCH) * CL;
};

template <int CL, int GCH>
static bool setup_cfg(cudaLaunchConfig_t& cfg, cudaLaunchAttribute* at, bool check)
{
    using C = Cfg<CL, GCH>;
    if (cudaFuncSetAttribute(ssm_kernel<CL, GCH>, cudaFuncAttributeMaxDynamicSharedMemorySize, C::SMEM) != cudaSuccess) { cudaGetLastError(); return false; }
    if (CL > 8 && cudaFuncSetAttribute(ssm_kernel<CL, GCH>, cudaFuncAttributeNonPortableClusterSizeAllowed, 1) != cudaSuccess) { cudaGetLastError(); return false; }
    cfg = cudaLaunchConfig_t{};
    cfg.gridDim = dim3(C::GRID); cfg.blockDim = dim3(C::NT); cfg.dynamicSmemBytes = C::SMEM; cfg.stream = cudaStreamPerThread;
    at[0].id = cudaLaunchAttributeClusterDimension;
    at[0].val.clusterDim.x = CL; at[0].val.clusterDim.y = 1; at[0].val.clusterDim.z = 1;
    cfg.attrs = at; cfg.numAttrs = 1;
    if (check) {
        int nc = 0;
        if (cudaOccupancyMaxActiveClusters(&nc, ssm_kernel<CL, GCH>, &cfg) != cudaSuccess) { cudaGetLastError(); return false; }
        if (nc < D_ / GCH) return false;
    }
    return true;
}

}

extern "C" void kernel_launch(void* const* d_in, const int* in_sizes, int n_in, void* d_out, int out_size)
{
    static int mode = -1;
    static cudaLaunchConfig_t cfg;
    static cudaLaunchAttribute at[1];
    if (mode < 0) {
        if (setup_cfg<16, 96>(cfg, at, true)) mode = 0;
        else { setup_cfg<8, 32>(cfg, at, false); mode = 1; }
    }
    const __nv_bfloat16* p[9];
    for (int i = 0; i < 9; i++) p[i] = (const __nv_bfloat16*)d_in[i];
    if (mode == 0)
        cudaLaunchKernelEx(&cfg, ssm_kernel<16, 96>, p[0], p[1], p[2], p[3], p[4], p[5], p[6], p[7], p[8], (__nv_bfloat16*)d_out);
    else
        cudaLaunchKernelEx(&cfg, ssm_kernel<8, 32>, p[0], p[1], p[2], p[3], p[4], p[5], p[6], p[7], p[8], (__nv_bfloat16*)d_out);
}
```

```cpp
#include <cuda_runtime.h>
#include <cuda_bf16.h>
#include <cuda_fp16.h>
#include <stdint.h>

namespace {

constexpr int L_ = 2048, D_ = 576, N_ = 128;

constexpr int CL = 16, GCH = 96, NS = 6, RPC = 128;
constexpr int NP = 3088, HB = 1536, UB_SIZE = 30976;
constexpr int X5_OFF = 0, XH5 = 1600, X3_OFF = 3200, X9_OFF = 6400, XH9 = 1088, X7_OFF = 8512, XV_OFF = 10624, W_SIZE = 12800;
constexpr int KS_SIZE = 16256;
constexpr int SLOT = W_SIZE + KS_SIZE;
constexpr int YP = 1552;
constexpr int YIN_OFF = UB_SIZE + NS * SLOT;
constexpr int MB_U = YIN_OFF + CL * YP, MB_Y = MB_U + 8;
constexpr int SMEM_BYTES = MB_U + 64;
constexpr int KG_SEED = 21, KG_FAC = 37 * 256;
constexpr int T4E = 0;
constexpr int T4Q = 4352;
constexpr int T4R = 6912;
constexpr int PQ = 9472;
constexpr int PR = 10048;
constexpr int XW = 10624;
constexpr int XK = 12192;
constexpr int P2E = 13136;
constexpr int P2O = 13928;
constexpr int PT3 = 14720;
constexpr int TSC = 16208;
constexpr int P2_OFF = 0, P2_PLANE = 816 * 4, ST_OFF = 2 * P2_PLANE;
#define NEK_ 6
constexpr int NEK = NEK_;

__device__ __forceinline__ uint32_t smem_u32(const void* p) { return (uint32_t)__cvta_generic_to_shared(p); }
__device__ __forceinline__ uint32_t mapa(uint32_t addr, uint32_t rank) {
    uint32_t r; asm volatile("mapa.shared::cluster.u32 %0, %1, %2;" : "=r"(r) : "r"(addr), "r"(rank)); return r;
}
__device__ __forceinline__ void mbar_init(uint32_t bar, uint32_t cnt) {
    asm volatile("mbarrier.init.shared::cta.b64 [%0], %1;" ::"r"(bar), "r"(cnt) : "memory");
}
__device__ __forceinline__ void mbar_arrive_tx(uint32_t bar, uint32_t bytes) {
    asm volatile("mbarrier.arrive.expect_tx.shared::cta.b64 _, [%0], %1;" ::"r"(bar), "r"(bytes) : "memory");
}
__device__ __forceinline__ void mbar_wait(uint32_t bar, uint32_t parity) {
    uint32_t ok; int it = 0;
    do {
        asm volatile("{\n.reg .pred p;\nmbarrier.try_wait.parity.shared::cta.b64 p, [%1], %2;\nselp.u32 %0, 1, 0, p;\n}"
                     : "=r"(ok) : "r"(bar), "r"(parity) : "memory");
        if (++it > (1 << 22)) __trap();
    } while (!ok);
}
__device__ __forceinline__ void nb_sync(int id) { asm volatile("bar.sync %0, 64;" ::"r"(id) : "memory"); }
__device__ __forceinline__ void nb_arrive(int id) { asm volatile("bar.arrive %0, 64;" ::"r"(id) : "memory"); }
__device__ __forceinline__ void cta_sync13() { asm volatile("bar.sync 13, 384;" ::: "memory"); }
__device__ __forceinline__ void cta_arrive13() { asm volatile("bar.arrive 13, 384;" ::: "memory"); }
__device__ __forceinline__ void ldsm4(uint32_t& r0, uint32_t& r1, uint32_t& r2, uint32_t& r3, uint32_t a) {
    asm volatile("ldmatrix.sync.aligned.m8n8.x4.shared.b16 {%0,%1,%2,%3}, [%4];" : "=r"(r0), "=r"(r1), "=r"(r2), "=r"(r3) : "r"(a) : "memory");
}
__device__ __forceinline__ void ldsm4t(uint32_t& r0, uint32_t& r1, uint32_t& r2, uint32_t& r3, uint32_t a) {
    asm volatile("ldmatrix.sync.aligned.m8n8.x4.trans.shared.b16 {%0,%1,%2,%3}, [%4];" : "=r"(r0), "=r"(r1), "=r"(r2), "=r"(r3) : "r"(a) : "memory");
}
__device__ __forceinline__ void ldsm2t(uint32_t& r0, uint32_t& r1, uint32_t a) {
    asm volatile("ldmatrix.sync.aligned.m8n8.x2.trans.shared.b16 {%0,%1}, [%2];" : "=r"(r0), "=r"(r1) : "r"(a) : "memory");
}
__device__ __forceinline__ void mma_bf16(float* c, uint32_t a0, uint32_t a1, uint32_t a2, uint32_t a3, uint32_t b0, uint32_t b1) {
    asm volatile("mma.sync.aligned.m16n8k16.row.col.f32.bf16.bf16.f32 {%0,%1,%2,%3},{%4,%5,%6,%7},{%8,%9},{%0,%1,%2,%3};"
                 : "+f"(c[0]), "+f"(c[1]), "+f"(c[2]), "+f"(c[3]) : "r"(a0), "r"(a1), "r"(a2), "r"(a3), "r"(b0), "r"(b1));
}
__device__ __forceinline__ void mma_sp(float* c, uint32_t a0, uint32_t a1, uint32_t a2, uint32_t a3, uint32_t b0, uint32_t b1, uint32_t b2, uint32_t b3, uint32_t e) {
    asm volatile("mma.sp::ordered_metadata.sync.aligned.m16n8k32.row.col.f32.bf16.bf16.f32 {%0,%1,%2,%3},{%4,%5,%6,%7},{%8,%9,%10,%11},{%0,%1,%2,%3},%12,0x0;"
                 : "+f"(c[0]), "+f"(c[1]), "+f"(c[2]), "+f"(c[3]) : "r"(a0), "r"(a1), "r"(a2), "r"(a3), "r"(b0), "r"(b1), "r"(b2), "r"(b3), "r"(e));
}
__device__ __forceinline__ void mma_f16(float* c, uint32_t a0, uint32_t a1, uint32_t a2, uint32_t a3, uint32_t b0, uint32_t b1) {
    asm volatile("mma.sync.aligned.m16n8k16.row.col.f32.f16.f16.f32 {%0,%1,%2,%3},{%4,%5,%6,%7},{%8,%9},{%0,%1,%2,%3};"
                 : "+f"(c[0]), "+f"(c[1]), "+f"(c[2]), "+f"(c[3]) : "r"(a0), "r"(a1), "r"(a2), "r"(a3), "r"(b0), "r"(b1));
}
__device__ __forceinline__ uint32_t lds32(uint32_t a) { uint32_t v; asm volatile("ld.shared.u32 %0, [%1];" : "=r"(v) : "r"(a) : "memory"); return v; }
__device__ __forceinline__ float lds32f(uint32_t a) { float v; asm volatile("ld.shared.f32 %0, [%1];" : "=f"(v) : "r"(a) : "memory"); return v; }
__device__ __forceinline__ float2 lds64f(uint32_t a) { float2 v; asm volatile("ld.shared.v2.f32 {%0,%1}, [%2];" : "=f"(v.x), "=f"(v.y) : "r"(a) : "memory"); return v; }
__device__ __forceinline__ uint2 lds64(uint32_t a) { uint2 v; asm volatile("ld.shared.v2.u32 {%0,%1}, [%2];" : "=r"(v.x), "=r"(v.y) : "r"(a) : "memory"); return v; }
__device__ __forceinline__ uint4 lds128(uint32_t a) { uint4 v; asm volatile("ld.shared.v4.u32 {%0,%1,%2,%3}, [%4];" : "=r"(v.x), "=r"(v.y), "=r"(v.z), "=r"(v.w) : "r"(a) : "memory"); return v; }
__device__ __forceinline__ void sts16(uint32_t a, uint16_t v) { asm volatile("st.shared.u16 [%0], %1;" ::"r"(a), "h"(v) : "memory"); }
__device__ __forceinline__ void sts32(uint32_t a, uint32_t v) { asm volatile("st.shared.u32 [%0], %1;" ::"r"(a), "r"(v) : "memory"); }
__device__ __forceinline__ void sts32f(uint32_t a, float v) { asm volatile("st.shared.f32 [%0], %1;" ::"r"(a), "f"(v) : "memory"); }
__device__ __forceinline__ void sts64(uint32_t a, uint32_t x, uint32_t y) { asm volatile("st.shared.v2.u32 [%0], {%1,%2};" ::"r"(a), "r"(x), "r"(y) : "memory"); }
__device__ __forceinline__ void sts64f(uint32_t a, float x, float y) { asm volatile("st.shared.v2.f32 [%0], {%1,%2};" ::"r"(a), "f"(x), "f"(y) : "memory"); }
__device__ __forceinline__ void sts128(uint32_t a, uint32_t x, uint32_t y, uint32_t z, uint32_t w) { asm volatile("st.shared.v4.u32 [%0], {%1,%2,%3,%4};" ::"r"(a), "r"(x), "r"(y), "r"(z), "r"(w) : "memory"); }

__device__ __forceinline__ uint32_t pack_bf16(float lo, float hi) {
    uint32_t r; asm("cvt.rn.bf16x2.f32 %0, %1, %2;" : "=r"(r) : "f"(hi), "f"(lo)); return r;
}
__device__ __forceinline__ uint16_t cvt_bf16(float v) { uint16_t r; asm("cvt.rn.bf16.f32 %0, %1;" : "=h"(r) : "f"(v)); return r; }
__device__ __forceinline__ uint32_t pack_f16(float lo, float hi) {
    uint32_t r; asm("cvt.rn.f16x2.f32 %0, %1, %2;" : "=r"(r) : "f"(hi), "f"(lo)); return r;
}
__device__ __forceinline__ uint32_t badd2(uint32_t a, uint32_t b) {
    __nv_bfloat162 r = __hadd2_rn(*reinterpret_cast<__nv_bfloat162*>(&a), *reinterpret_cast<__nv_bfloat162*>(&b));
    return *reinterpret_cast<uint32_t*>(&r);
}
__device__ __forceinline__ uint32_t bmul2(uint32_t a, uint32_t b) {
    __nv_bfloat162 r = __hmul2_rn(*reinterpret_cast<__nv_bfloat162*>(&a), *reinterpret_cast<__nv_bfloat162*>(&b));
    return *reinterpret_cast<uint32_t*>(&r);
}
__device__ __forceinline__ uint32_t shift1(uint32_t a, uint32_t b) { return __byte_perm(a, b, 0x5432); }

__device__ __forceinline__ float shf(float v, int src) { return __shfl_sync(0xffffffffu, v, src); }
__device__ __forceinline__ uint32_t shu(uint32_t v, int src) { return __shfl_sync(0xffffffffu, v, src); }
__device__ __forceinline__ void stsm4t(uint32_t a, uint32_t r0, uint32_t r1, uint32_t r2, uint32_t r3) {
    asm volatile("stmatrix.sync.aligned.m8n8.x4.trans.shared.b16 [%0], {%1,%2,%3,%4};" ::"r"(a), "r"(r0), "r"(r1), "r"(r2), "r"(r3) : "memory");
}
__device__ __forceinline__ void bulk_s2c(uint32_t dst, uint32_t src, uint32_t bytes, uint32_t mb) {
    asm volatile("cp.async.bulk.shared::cluster.shared::cta.mbarrier::complete_tx::bytes [%0], [%1], %2, [%3];"
                 ::"r"(dst), "r"(src), "r"(bytes), "r"(mb) : "memory");
}
__device__ __forceinline__ void cl_arrive() { asm volatile("barrier.cluster.arrive.relaxed.aligned;" ::: "memory"); }
__device__ __forceinline__ void cl_wait() { asm volatile("barrier.cluster.wait.acquire.aligned;" ::: "memory"); }

struct H2C { __half2 r, i; };
__device__ __forceinline__ H2C hc_mul(const H2C& a, const H2C& b) {
    H2C o;
    o.r = __hfma2(a.r, b.r, __hneg2(__hmul2(a.i, b.i)));
    o.i = __hfma2(a.r, b.i, __hmul2(a.i, b.r));
    return o;
}
__device__ __forceinline__ H2C hc_mulc(const H2C& a, const H2C& e) {
    H2C o;
    o.r = __hfma2(a.r, e.r, __hmul2(a.i, e.i));
    o.i = __hfma2(a.i, e.r, __hneg2(__hmul2(a.r, e.i)));
    return o;
}
__device__ __forceinline__ uint32_t h2u(__half2 h) { return *reinterpret_cast<uint32_t*>(&h); }
__device__ __forceinline__ __half2 u2h(uint32_t u) { return *reinterpret_cast<__half2*>(&u); }
__device__ __forceinline__ float2 csq(float2 a) { return make_float2(fmaf(a.x, a.x, -a.y * a.y), (a.x + a.x) * a.y); }
__device__ __forceinline__ H2C hpack(float2 a, float2 b) { H2C o; o.r = u2h(pack_f16(a.x, b.x)); o.i = u2h(pack_f16(a.y, b.y)); return o; }
__device__ __forceinline__ float ex2f(float x) { float r; asm("ex2.approx.ftz.f32 %0, %1;" : "=f"(r) : "f"(x)); return r; }
__device__ __forceinline__ float bf_lo(uint32_t v) { return __uint_as_float(v << 16); }
__device__ __forceinline__ float bf_hi(uint32_t v) { return __uint_as_float(v & 0xffff0000u); }

#define TL(i)
#define TLG(i)

__device__ __forceinline__ void exp_pair(float zr2  , float ph, float pl, float mult, float2& E) {
    float p = ph * mult;
    float r = (p - rintf(p)) + pl * mult;
    float ang = r * 6.283185307179586f;
    float m = ex2f(zr2 * mult);
    E.x = m * __cosf(ang);
    E.y = m * __sinf(ang);
}

__device__ __forceinline__ void prep(uint32_t S, int lane, const uint32_t* __restrict__ pv, uint32_t ldtb, float& isc, float& gmaxo, int grp)
{
    float dt;
    {
        const float ldt = __uint_as_float(ldtb << 16);
        float e = expf(ldt);
        uint32_t b = __float_as_uint(e);
        int low = (int)(b & 0xffffu) - 0x8000;
        if (low >= -4 && low <= 4) e = (float)exp((double)ldt);
        dt = __bfloat162float(__float2bfloat16_rn(e));
    }
    float zr[2], zi[2]; float2 cb[2];
    #pragma unroll
    for (int k = 0; k < 2; k++) {
        float are = k ? bf_hi(pv[0]) : bf_lo(pv[0]);
        float aim = k ? bf_hi(pv[1]) : bf_lo(pv[1]);
        float bre = k ? bf_hi(pv[2]) : bf_lo(pv[2]);
        float bim = k ? bf_hi(pv[3]) : bf_lo(pv[3]);
        float cre = k ? bf_hi(pv[4]) : bf_lo(pv[4]);
        float cim = k ? bf_hi(pv[5]) : bf_lo(pv[5]);
        zr[k] = dt * are; zi[k] = dt * aim;
        float dbr = dt * bre, dbi = dt * bim;
        cb[k].x = fmaf(cre, dbr, -cim * dbi);
        cb[k].y = fmaf(cre, dbi, cim * dbr);
    }
    float gmax = fmaxf(fmaxf(zr[0], zr[1]), 0.f);
    float cmax = fmaxf(fmaxf(fabsf(cb[0].x), fabsf(cb[0].y)), fmaxf(fabsf(cb[1].x), fabsf(cb[1].y)));
    gmax = __uint_as_float(__reduce_max_sync(0xffffffffu, __float_as_uint(gmax)));
    int ex = (int)(__reduce_max_sync(0xffffffffu, __float_as_uint(cmax)) >> 23);
    ex = min(max(ex, 30), 230);
    const float sc = __uint_as_float((uint32_t)(127 + 10 + 127 - ex) << 23);
    isc = __uint_as_float((uint32_t)(ex - 10) << 23);
    gmaxo = gmax;

    float2 E1[2], E256[2];
    #pragma unroll
    for (int k = 0; k < 2; k++) {
        const float C1 = 0.15915494309189535f;
        const float C2 = (float)(0.15915494309189533576888 - (double)0.15915494309189535f);
        float ph = zi[k] * C1;
        float pl = fmaf(zi[k], C1, -ph) + zi[k] * C2;
        float z2 = (zr[k] - gmax) * 1.4426950408889634f;
        exp_pair(z2, ph, pl, 1.f, E1[k]);
        exp_pair(z2, ph, pl, 256.f, E256[k]);
    }
    const uint32_t wr = S + lane * 4;
    auto put = [&](int row, const H2C& v) {
        const uint32_t a = (wr ^ ((row & 7) << 4)) + row * 256;
        sts32(a, h2u(v.r)); sts32(a + 128, h2u(v.i));
    };
    float2 a[2];
    H2C h1 = hpack(E1[0], E1[1]);
    a[0] = csq(E1[0]); a[1] = csq(E1[1]); H2C h2 = hpack(a[0], a[1]);
    a[0] = csq(a[0]); a[1] = csq(a[1]); H2C h4 = hpack(a[0], a[1]);
    a[0] = csq(a[0]); a[1] = csq(a[1]); H2C h8 = hpack(a[0], a[1]);
    a[0] = csq(a[0]); a[1] = csq(a[1]); H2C h16 = hpack(a[0], a[1]);
    a[0] = csq(a[0]); a[1] = csq(a[1]); H2C h32 = hpack(a[0], a[1]);
    a[0] = csq(a[0]); a[1] = csq(a[1]); H2C h64 = hpack(a[0], a[1]);
    a[0] = csq(a[0]); a[1] = csq(a[1]); H2C h128 = hpack(a[0], a[1]);
    {
        float2 c0 = make_float2(cb[0].x * sc, -cb[0].y * sc), c1 = make_float2(cb[1].x * sc, -cb[1].y * sc);
        H2C s[4];
        s[0] = hpack(c0, c1);
        s[1] = hc_mulc(s[0], h8); s[2] = hc_mulc(s[0], h16); s[3] = hc_mulc(s[1], h16);
        #pragma unroll
        for (int k = 0; k < 4; k++) {
            const int row = KG_SEED + (k & 1) + 8 * (k >> 1);
            H2C t1 = hc_mulc(s[k], h64), t2 = hc_mulc(s[k], h128);
            put(row, s[k]); put(row + 2, t1); put(row + 4, t2); put(row + 6, hc_mulc(t1, h128));
        }
    }
    sts64(S + KG_FAC + lane * 8, h2u(h32.r), h2u(h32.i));
    { H2C h0; h0.r = u2h(0x3c003c00u); h0.i = u2h(0u); put(0, h0); }
    put(1, h1); put(2, h2); put(4, h4);
    H2C h3 = hc_mul(h1, h2); put(3, h3);
    put(5, hc_mul(h4, h1));
    H2C h6 = hc_mul(h4, h2); put(6, h6);
    put(7, hc_mul(h4, h3));
    H2C h256 = hpack(E256[0], E256[1]);
    put(8, h256); put(10, hc_mul(h256, h2)); put(12, hc_mul(h256, h4)); put(14, hc_mul(h256, h6));
    a[0] = csq(E256[0]); a[1] = csq(E256[1]); H2C h512 = hpack(a[0], a[1]);
    H2C h768 = hc_mul(h512, h256);
    put(9, h512); put(11, hc_mul(h512, h4)); put(13, h768); put(15, hc_mul(h768, h4));
    a[0] = csq(a[0]); a[1] = csq(a[1]); H2C h1024 = hpack(a[0], a[1]);
    put(16, h1024); put(17, hc_mul(h1024, h256)); put(18, hc_mul(h1024, h512)); put(19, hc_mul(h1024, h768));
    a[0] = csq(a[0]); a[1] = csq(a[1]); put(20, hpack(a[0], a[1]));
    if (grp == 0) asm volatile("bar.arrive 14, 256;" ::: "memory");
    else if (grp == 1) asm volatile("bar.arrive 15, 256;" ::: "memory");
}

__device__ __forceinline__ void kmma(uint32_t S, int lane, float isc, float gmax, float (&acc)[2][3][4])
{
    const int q = lane & 3;
    #pragma unroll
    for (int i = 0; i < 2; i++)
        #pragma unroll
        for (int j = 0; j < 3; j++)
            #pragma unroll
            for (int k = 0; k < 4; k++) acc[i][j][k] = 0.f;
    const int mi = lane >> 3, r = lane & 7;
    const int rowA = KG_SEED + (mi & 1) * 8 + r;
    const int row2 = (r == 1) ? 20 : 16 + (r >> 1);
    const uint32_t aA = S + rowA * 256 + (mi >> 1) * 128 + ((rowA & 7) << 4);
    const uint32_t aB = S + ((mi >> 1) * 8 + r) * 256 + (mi & 1) * 128 + (r << 4);
    const uint32_t aC = (S + row2 * 256 + (mi & 1) * 128 + ((row2 & 7) << 4)) ^ ((mi >> 1) << 4);
    const uint32_t aF = S + KG_FAC + q * 8;
    #pragma unroll
    for (int ks = 0; ks < 8; ks += 2) {
        uint32_t c[4];
        ldsm4(c[0], c[1], c[2], c[3], aC ^ (ks << 4));
        #pragma unroll
        for (int k2 = 0; k2 < 2; k2++) {
            uint32_t a0, a1, a2, a3, b00, b01, b10, b11;
            ldsm4(a0, a1, a2, a3, aA ^ ((ks + k2) << 4));
            ldsm4(b00, b01, b10, b11, aB ^ ((ks + k2) << 4));
            const uint2 f0 = lds64(aF + (ks + k2) * 32);
            H2C f; f.r = u2h(f0.x); f.i = u2h(f0.y);
            H2C s0; s0.r = u2h(a0); s0.i = u2h(a2);
            H2C s1; s1.r = u2h(a1); s1.i = u2h(a3);
            const H2C t0 = hc_mulc(s0, f), t1 = hc_mulc(s1, f);
            mma_f16(acc[0][0], a0, a1, a2, a3, b00, b01);
            mma_f16(acc[0][1], a0, a1, a2, a3, b10, b11);
            mma_f16(acc[0][2], a0, a1, a2, a3, c[2 * k2], c[2 * k2 + 1]);
            mma_f16(acc[1][0], h2u(t0.r), h2u(t1.r), h2u(t0.i), h2u(t1.i), b00, b01);
            mma_f16(acc[1][1], h2u(t0.r), h2u(t1.r), h2u(t0.i), h2u(t1.i), b10, b11);
            mma_f16(acc[1][2], h2u(t0.r), h2u(t1.r), h2u(t0.i), h2u(t1.i), c[2 * k2], c[2 * k2 + 1]);
        }
    }
    if (gmax > 0.f) {
        const float g2 = gmax * 1.4426950408889634f;
        const int seed0 = 64 * (lane >> 3) + 8 * ((lane >> 2) & 1);
        #pragma unroll
        for (int i = 0; i < 2; i++)
            #pragma unroll
            for (int t = 0; t < 3; t++)
                #pragma unroll
                for (int k = 0; k < 4; k++) {
                    const int b = k & 1;
                    int l = seed0 + 16 * ((k >> 1) + 2 * i);
                    if (t == 0) l += 2 * q + b;
                    else if (t == 1) l += b ? (512 + 256 * (q >> 1) + 4 * (q & 1)) : (256 + 2 * q);
                    else l += b ? 2048 : (1024 + 256 * q);
                    acc[i][t][k] *= isc * exp2f(g2 * (float)l);
                }
    } else {
        #pragma unroll
        for (int i = 0; i < 2; i++)
            #pragma unroll
            for (int t = 0; t < 3; t++)
                #pragma unroll
                for (int k = 0; k < 4; k++) acc[i][t][k] *= isc;
    }
}

__device__ __forceinline__ void ktables(uint32_t KS, int lane, const float (&fe)[4], const float (&fo)[4], float (&fu)[4], float k512)
{
    const int a = lane >> 3, r = lane & 7;
    const bool r7 = (r == 7), l31 = (lane == 31);
    const int sp = (r > 0) ? lane - 1 : lane + 7;
    const int s0 = (lane + 31) & 31;
    {
        const uint32_t z = KS + (lane & 15) * 16;
        sts128((lane < 16) ? z + T4E : z + T4E + 256 * 16, 0u, 0u, 0u, 0u);
        sts128((lane < 16) ? z + T4Q : z + T4R, 0u, 0u, 0u, 0u);
        sts128(KS + PQ + lane * 16, 0u, 0u, 0u, 0u); sts128(KS + PQ + 512 + lane * 16, 0u, 0u, 0u, 0u);
        if (lane < 8) sts128(KS + PQ + 1024 + lane * 16, 0u, 0u, 0u, 0u);
    }
    if (l31) fu[3] -= k512;
    auto pred = [&](const float (&x)[4], float wrapv, float (&o)[4]) {
        o[0] = shf(r7 ? (l31 ? wrapv : x[3]) : x[0], s0);
        #pragma unroll
        for (int j = 1; j < 4; j++) o[j] = shf(r7 ? x[j - 1] : x[j], sp);
    };
    float A[4], B[4], C[4], Pu[4];
    pred(fe, 0.f, A); pred(fo, 0.f, B); pred(fu, fe[3], Pu); pred(B, 0.f, C);
    uint32_t We[4], Wq[4], Wr[4], Wu[4];
    float d[4];
    #pragma unroll
    for (int j = 0; j < 4; j++) {
        We[j] = pack_bf16(fe[j], A[j]);
        Wr[j] = pack_bf16(fo[j] - fe[j], B[j] - A[j]);
        Wq[j] = pack_bf16(B[j] - fe[j], C[j] - A[j]);
        Wu[j] = pack_bf16(fu[j], Pu[j]);
        d[j] = fu[j] - Pu[j];
    }
    uint32_t Xq[2], Xr[2];
    {
        const uint32_t D01 = pack_bf16(d[0], d[1]), D12 = pack_bf16(d[1], d[2]);
        const uint32_t Dp = shu(r7 ? (D01 << 16) : D01, sp);
        const uint32_t Dn = shu((r == 0) ? D12 : D01, (r < 7) ? lane + 1 : lane - 7);
        const bool odd = r & 1;
        const uint32_t sq = (odd ? D01 : Dp) ^ 0x80008000u, sr = odd ? Dn : D01;
        Xq[0] = odd ? (sq & 0xffffu) : (sq << 16); Xq[1] = odd ? (sq >> 16) : (sq & 0xffff0000u);
        Xr[0] = odd ? (sr & 0xffffu) : (sr << 16); Xr[1] = odd ? (sr >> 16) : (sr & 0xffff0000u);
        const float q128 = shf(fo[3], 31) - shf(fu[0], 0);
        const uint32_t q128b = cvt_bf16(q128);
        const uint32_t w3q = shu(Wq[3], 31), w3r = shu(Wr[3], 31);
        if (lane == 0) { Xq[0] = __byte_perm(q128b, w3q, 0x5410); Xr[0] = w3r << 16; }
        if (lane == 1) Xq[0] |= q128b << 16;
    }
    __syncwarp();
    uint32_t ad[4];
    #pragma unroll
    for (int s = 0; s < 4; s++) {
        const int dd = (s + a) & 3;
        ad[s] = KS + (32 * a + r + 8) * 16 + dd * 4 + (dd == 1 ? -128 : (dd == 2 ? 128 : 0));
    }
    #pragma unroll
    for (int j = 0; j < 4; j++)
        #pragma unroll
        for (int s = 0; s < 4; s++) {
            sts32(ad[s] + T4E + 128 * j, We[j]);
            sts32(ad[s] + T4Q + 128 * j, Wq[j]);
            sts32(ad[s] + T4R + 128 * j, Wr[j]);
            sts32(ad[s] + T4E + 2048 + 128 * j, Wu[j]);
        }
    if (a == 0) {
        #pragma unroll
        for (int j = 0; j < 2; j++)
            #pragma unroll
            for (int s = 0; s < 4; s++) { sts32(ad[s] + T4Q + 2048 + 128 * j, Xq[j]); sts32(ad[s] + T4R + 2048 + 128 * j, Xr[j]); }
    }
    if (l31) {
        const uint16_t b = (uint16_t)(Wu[3] & 0xffffu);
        sts16(KS + T4E + 264 * 16 + 2, b); sts16(KS + T4E + 264 * 16 + 14, b); sts16(KS + T4E + 256 * 16 + 6, b);
        const uint16_t nb = b ^ 0x8000u;
        const uint32_t p = KS + PR + (127 - 60) * 8;
        sts16(p, nb); sts16(p - 28, nb); sts16(p + 10, nb); sts16(p - 18, nb);
    }
    {
        const uint32_t p = KS + ((r & 1) ? PQ : PR) + (4 + 16 * a + ((r - 1) >> 1)) * 8;
        const float sg = (r & 1) ? -1.f : 1.f;
        #pragma unroll
        for (int j = 0; j < 4; j++) {
            const uint16_t b = cvt_bf16(d[j] * sg);
            if (j > 0 || lane != 0) { sts16(p + 32 * j, b); sts16(p + 32 * j - 28, b); sts16(p + 32 * j + 10, b); sts16(p + 32 * j - 18, b); }
        }
    }
}

__device__ __forceinline__ void wtables(uint32_t KS, int lane, const float (&v2)[4], const float (&v3)[4], float k2048)
{
    const int a = lane >> 3, e = (lane >> 2) & 1, q = lane & 3;
    #pragma unroll
    for (int i = 0; i < 6; i++) sts128(KS + P2E + (lane + 32 * i) * 16, 0u, 0u, 0u, 0u);
    __syncwarp();
    {
        const uint32_t p = KS + ((q & 1) ? P2O : P2E) + (36 * (q >> 1) + 9 * a + e + 18) * 8;
        const uint32_t pa = p - ((q & 1) ? 68 : 0), pb = p - ((q & 1) ? 0 : 68);
        #pragma unroll
        for (int j = 0; j < 4; j++) {
            const uint16_t b = cvt_bf16(v2[j]);
            const uint32_t c8 = (j == 3) ? e * 8 : 0;
            sts16(pa + 16 * j, b); sts16(pb + 16 * j, b); sts16(pa + 16 * j + 10 + c8, b); sts16(pb + 16 * j + 10 + c8, b);
        }
    }
    {
        const uint32_t p = KS + PT3 + (36 + 36 * q + 9 * a + e) * 8;
        const uint32_t pa = p - (e ? 68 : 0), pb = p - (e ? 0 : 68);
        #pragma unroll
        for (int j = 0; j < 4; j++) {
            const uint16_t b = cvt_bf16(v3[j]);
            const int c = (j == 3) ? 26 : 18;
            if (j > 0 || lane != 0) { sts16(pa + 16 * j, b); sts16(pb + 16 * j, b); sts16(pa + 16 * j + c, b); sts16(pb + 16 * j + c, b); }
        }
    }
    if (lane == 0) {
        const uint16_t b = cvt_bf16(k2048);
        const uint32_t p = KS + PT3 + 180 * 8;
        sts16(p, b); sts16(p - 68, b); sts16(p + 18, b); sts16(p - 50, b);
        sts64(KS + TSC, (uint32_t)cvt_bf16(v3[0]), __float_as_uint(v2[0]));
    }
}

__host__ __device__ constexpr int tile_n(int b) { return b >= 0 ? b / 8 : -((7 - b) / 8); }
__host__ __device__ constexpr int tile_off(int b) { return tile_n(b) * NP + ((b - 8 * tile_n(b)) >> 2) * HB + ((b - 8 * tile_n(b)) & 3) * 32; }

template <int E0, int NE>
__device__ __forceinline__ void hconv(uint32_t U, uint32_t KS, int lane, uint32_t dbits, float (&aP)[NE][4], float (&aQ)[NE][4], float (&aR)[NE][4])
{
    const int g = lane >> 2, q = lane & 3;
    const uint32_t rowb = U + (lane & 7) * NP;
    const uint32_t ub = rowb + (lane >> 4) * 128 + ((lane >> 3) & 1) * 16;
    const uint32_t uq = rowb + (lane >> 3) * 16, uq2 = uq + (lane >> 4) * (HB - 128), uq3 = uq + (lane >> 4) * (NP - HB - 128);
    const uint32_t dA = (g == 2 * q) ? dbits : ((g == 2 * q + 1) ? (dbits << 16) : 0u);
    const uint32_t tb = KS + (g - 2 * q + 8) * 16;
    const uint32_t pb = KS + (((g + 1) >> 1) - 2 * q - 69 + 80) * 8;
    const uint32_t meta = (g & 1) ? 0x88888888u : 0xDDDDDDDDu;
    #pragma unroll
    for (int e = 0; e < NE; e++)
        #pragma unroll
        for (int k = 0; k < 4; k++) { aP[e][k] = 0.f; aQ[e][k] = 0.f; aR[e][k] = 0.f; }
    constexpr int B0 = E0 - 16;
    uint32_t xe[NE + 16][2], xo[NE + 16][2], xs[NE + 16][2];
    uint32_t qo[NE + 6][4], qe[NE + 6][4];
    auto ldtile = [&](int b) {
        const int i = b - B0;
        ldsm4(xe[i][0], xe[i][1], xo[i][0], xo[i][1], ub + tile_off(b));
        xs[i][0] = badd2(xe[i][0], xo[i][0]); xs[i][1] = badd2(xe[i][1], xo[i][1]);
    };
    auto ldquad = [&](int b) {
        const int i = b - B0;
        const int df = tile_off(b + 1) - tile_off(b);
        const uint32_t ad = ((df == 32) ? uq : (df == HB - 96 ? uq2 : uq3)) + tile_off(b);
        ldsm4(qe[i][0], qe[i][1], qe[i][2], qe[i][3], ad);
        ldsm4(qo[i][0], qo[i][1], qo[i][2], qo[i][3], ad + 128);
        if (b < E0 - 9) { xs[i][0] = badd2(qe[i][0], qo[i][0]); xs[i][1] = badd2(qe[i][1], qo[i][1]); }
    };
    uint4 fE = lds128(tb + T4E), fQ = lds128(tb + T4Q), fR = lds128(tb + T4R);
    #pragma unroll
    for (int e = 0; e < NE; e++) ldtile(E0 + e);
    #pragma unroll
    for (int e = 0; e < NE; e++) {
        mma_bf16(aQ[e], dA, 0u, 0u, dA, xe[e + 16][0], xe[e + 16][1]);
        mma_bf16(aR[e], dA, 0u, 0u, dA, xo[e + 16][0], xo[e + 16][1]);
    }
    #pragma unroll
    for (int m = 0; m <= 9; m++) {
        const uint4 cE = fE, cQ = fQ, cR = fR;
        fE = lds128(tb + T4E + 256 * (m + 1));
        if (m < 8) { fQ = lds128(tb + T4Q + 256 * (m + 1)); fR = lds128(tb + T4R + 256 * (m + 1)); }
        if (m < 9) ldtile(E0 - m - 1);
        else {
            #pragma unroll
            for (int b = E0 - 10; b <= E0 + NE - 11; b++) ldquad(b);
        }
        #pragma unroll
        for (int e = 0; e < NE; e++) { const int i = e - m + 16; mma_bf16(aP[e], cE.x, cE.y, cE.z, cE.w, xs[i][0], xs[i][1]); }
        if (m <= 8) {
            #pragma unroll
            for (int e = 0; e < NE; e++) { const int i = e - m + 16; mma_bf16(aQ[e], cQ.x, cQ.y, cQ.z, cQ.w, xo[i][0], xo[i][1]); }
            #pragma unroll
            for (int e = 0; e < NE; e++) { const int i = e - m + 16; mma_bf16(aR[e], cR.x, cR.y, cR.z, cR.w, xe[i][0], xe[i][1]); }
        }
    }
    #pragma unroll
    for (int m = 10; m <= 16; m++) {
        const uint4 cE = fE;
        if (m < 16) { fE = lds128(tb + T4E + 256 * (m + 1)); ldquad(E0 - m - 1); }
        if ((m & 1) == 0) {
            const uint2 g1 = lds64(pb + PQ + (8 * m - 80 + 8) * 8), g0 = lds64(pb + PQ + (8 * m - 80) * 8);
            const uint2 h1 = lds64(pb + PR + (8 * m - 80 + 8) * 8), h0 = lds64(pb + PR + (8 * m - 80) * 8);
            #pragma unroll
            for (int e = 0; e < NE; e++) { const int i = e - m + 16; mma_bf16(aP[e], cE.x, cE.y, cE.z, cE.w, xs[i][0], xs[i][1]); }
            #pragma unroll
            for (int e = 0; e < NE; e++) { const int i = e - m + 16; mma_sp(aQ[e], g1.x, g1.y, g0.x, g0.y, qo[i][0], qo[i][1], qo[i][2], qo[i][3], meta); }
            #pragma unroll
            for (int e = 0; e < NE; e++) { const int i = e - m + 16; mma_sp(aR[e], h1.x, h1.y, h0.x, h0.y, qe[i][0], qe[i][1], qe[i][2], qe[i][3], meta); }
        } else {
            #pragma unroll
            for (int e = 0; e < NE; e++) { const int i = e - m + 16; mma_bf16(aP[e], cE.x, cE.y, cE.z, cE.w, xs[i][0], xs[i][1]); }
        }
    }
}

template <int E0, int NE>
__device__ __forceinline__ void hfinal(uint32_t U, uint32_t KS, uint32_t W, int lane, float (&aP)[NE][4], float (&aQ)[NE][4], float (&aR)[NE][4])
{
    const int g = lane >> 2, q = lane & 3;
    const uint32_t pb = W + P2_OFF + (132 * (2 * q - 2) + g) * 4;
    const uint32_t sb = W + ST_OFF + (132 * 2 * q + g) * 4;
    #pragma unroll
    for (int e = 0; e < NE; e++) {
        #pragma unroll
        for (int k = 0; k < 4; k++) {
            const int w = 132 * (k & 1) + 16 * (E0 + e) + 8 * (k >> 1);
            float y0 = aP[e][k] + aQ[e][k], y1 = aP[e][k] + aR[e][k];
            if (q > 0) { y0 += lds32f(pb + w * 4); y1 += lds32f(pb + w * 4 + P2_PLANE); }
            if (E0 + e == 7 && k == 3) {
                if (lane == 28) {
                    const float k512 = lds32f(KS + TSC + 4);
                    const float u0 = bf_lo(lds32(U)), u1 = bf_lo(lds32(U + 128));
                    y0 = fmaf(k512, u0, y0); y1 = fmaf(k512, u0 + u1, y1);
                }
            }
            sts32(sb + w * 4, pack_bf16(y0, y1));
        }
    }
}

__device__ __forceinline__ void s23(uint32_t W, uint32_t KS, int lane)
{
    const int g = lane >> 2, q = lane & 3;
    float acc[12][4];
    #pragma unroll
    for (int i = 0; i < 12; i++)
        #pragma unroll
        for (int k = 0; k < 4; k++) acc[i][k] = 0.f;
    const int k16 = lane & 15, mi = lane >> 3;
    {
        uint2 e1[5], e0[5], o1[5], o0[5];
        const int xi0 = g - 2 * q + 16;
        const uint32_t fb = KS + (xi0 + (xi0 >> 3)) * 8;
        #pragma unroll
        for (int d = 0; d < 5; d++) {
            e1[d] = lds64(fb + P2E + 144 * d); e0[d] = lds64(fb + P2E + 144 * d - 72);
            o1[d] = lds64(fb + P2O + 144 * d); o0[d] = lds64(fb + P2O + 144 * d - 72);
        }
        const uint32_t xb = W + ((mi >> 1) ? X3_OFF : X5_OFF) + (k16 & 1) * XH5 + ((k16 >> 1) + 1) * 16;
        {
            uint32_t b0, b1;
            ldsm2t(b0, b1, W + X5_OFF + (k16 == 15 ? XH5 : 0));
            #pragma unroll
            for (int d = 1; d <= 4; d++) mma_bf16(acc[d - 1], e1[d].x, e1[d].y, e0[d].x, e0[d].y, b0, b1);
        }
        #pragma unroll
        for (int kap = 0; kap < 12; kap++) {
            uint32_t x0, x1, y0, y1;
            ldsm4t(x0, x1, y0, y1, xb + kap * 128);
            #pragma unroll
            for (int d = 0; d <= 4; d++) if (kap + d < 12) mma_bf16(acc[kap + d], e1[d].x, e1[d].y, e0[d].x, e0[d].y, x0, x1);
            #pragma unroll
            for (int d = 0; d <= 4; d++) if (kap + d < 12) mma_bf16(acc[kap + d], o1[d].x, o1[d].y, o0[d].x, o0[d].y, y0, y1);
        }
    }
    {
        uint2 G9[9], G7[9];
        const int xi9 = 32 + 2 * ((g + 1) >> 1) - 4 * q, xi7 = 32 + 2 * (g >> 1) - 4 * q + 1;
        const uint32_t g9 = KS + PT3 + (xi9 + (xi9 >> 3)) * 8, g7 = KS + PT3 + (xi7 + (xi7 >> 3)) * 8;
        const uint32_t m9 = (g & 1) ? 0x88888888u : 0xDDDDDDDDu, m7 = (g & 1) ? 0xDDDDDDDDu : 0x88888888u;
        const uint32_t xb = W + X9_OFF + (lane & 1) * XH9 + (lane >> 1) * 16;
        uint2 A9[8][2], A7[8][2];
        #pragma unroll
        for (int D = 0; D < 8; D++) {
            A9[D][0] = lds64(g9 + 144 * D); A9[D][1] = lds64(g9 + 144 * D - 144);
            A7[D][0] = lds64(g7 + 144 * D); A7[D][1] = lds64(g7 + 144 * D - 144);
        }
        (void)G9; (void)G7;
        #pragma unroll
        for (int kp = 0; kp < 4; kp++) {
            uint32_t b[4], c[4];
            ldsm4t(b[0], b[1], b[2], b[3], xb + kp * 256);
            ldsm4t(c[0], c[1], c[2], c[3], xb + (X7_OFF - X9_OFF) + kp * 256);
            #pragma unroll
            for (int rp = 2 * kp; rp < 8; rp++) {
                const int D = rp - 2 * kp;
                mma_sp(acc[rp + 4], A9[D][0].x, A9[D][0].y, A9[D][1].x, A9[D][1].y, b[0], b[1], b[2], b[3], m9);
            }
            #pragma unroll
            for (int rp = 2 * kp; rp < 8; rp++) {
                const int D = rp - 2 * kp;
                mma_sp(acc[rp + 4], A7[D][0].x, A7[D][0].y, A7[D][1].x, A7[D][1].y, c[0], c[1], c[2], c[3], m7);
            }
        }
    }
    {
        const uint32_t kk = lds32(KS + TSC);
        const uint32_t ad = (g == 2 * q) ? kk : ((g == 2 * q + 1) ? (kk << 16) : 0u);
        const uint32_t xb = W + XV_OFF + (k16 & 1) * XH9 + ((k16 >> 1) + 1) * 16;
        #pragma unroll
        for (int rho = 3; rho < 12; rho++) {
            uint32_t b0, b1;
            ldsm2t(b0, b1, rho == 3 ? (W + XV_OFF + (k16 == 15 ? XH9 : 0)) : (xb + (rho - 4) * 128));
            mma_bf16(acc[rho], ad, 0u, 0u, ad, b0, b1);
        }
    }
    __syncwarp();
    const uint32_t pb = W + P2_OFF + (q >> 1) * P2_PLANE + (4 * g + 2 * (q & 1)) * 4;
    #pragma unroll
    for (int rho = 0; rho < 12; rho++) {
        sts64f(pb + (64 * rho + 4 * (rho >> 1)) * 4, acc[rho][0], acc[rho][1]);
        sts64f(pb + (64 * rho + 32 + 4 * (rho >> 1)) * 4, acc[rho][2], acc[rho][3]);
    }
}

template <bool FULL>
__device__ __forceinline__ void wgen_pass(uint32_t U, uint32_t W, int lam, int lane)
{
    const uint32_t a0 = U + (lam >> 4) * NP + ((lane >> 3) & 1) * HB + (lane & 7) * 16;
    const uint32_t aL = a0 - ((lane & 7) ? 8 : ((lane & 8) ? HB - 120 : NP - HB - 120));
    const uint32_t aR = a0 + (((lane & 7) != 7) ? 16 : ((lane & 8) ? NP - HB - 112 : HB - 112));
    uint32_t e[7], o[7];
    { uint2 t = lds64(aL); e[0] = t.x; e[1] = t.y; }
    { uint4 t = lds128(a0); e[2] = t.x; e[3] = t.y; e[4] = t.z; e[5] = t.w; }
    e[6] = lds32(aR);
    { uint2 t = lds64(aL + 128); o[0] = t.x; o[1] = t.y; }
    { uint4 t = lds128(a0 + 128); o[2] = t.x; o[3] = t.y; o[4] = t.z; o[5] = t.w; }
    o[6] = lds32(aR + 128);
    uint32_t sA[7], sB[6], eB[6], oB[5];
    #pragma unroll
    for (int w = 1; w < 7; w++) sA[w] = badd2(e[w], o[w]);
    #pragma unroll
    for (int w = 1; w < 6; w++) { sB[w] = shift1(sA[w], sA[w + 1]); eB[w] = shift1(e[w], e[w + 1]); }
    #pragma unroll
    for (int w = 0; w < 5; w++) oB[w] = shift1(o[w], o[w + 1]);
    uint32_t x5e[4], x5o[4], x3e[4], x3o[4], x7e[4], x7o[4], x9e[4], x9o[4], xve[4];
    #pragma unroll
    for (int k = 0; k < 4; k++) {
        const int w = k + 2;
        const uint32_t d1 = badd2(sB[w - 1], sA[w]), d2 = badd2(sA[w], sB[w]);
        x5e[k] = badd2(d1, eB[w]); x5o[k] = badd2(oB[w - 1], d2);
        x3e[k] = badd2(oB[w - 2], sA[w - 1]); x3o[k] = badd2(sA[w - 1], eB[w - 1]);
        if (FULL) {
            const uint32_t t3 = badd2(d1, sB[w]);
            x7e[k] = badd2(o[w - 1], t3); x7o[k] = badd2(t3, e[w + 1]);
            x9e[k] = badd2(sA[w - 1], x7o[k]); x9o[k] = badd2(x7e[k], sA[w + 1]);
            xve[k] = badd2(sA[w - 1], x5e[k]);
        }
    }
    const uint32_t w5 = W + (lam + 1) * 16;
    sts128(w5 + X5_OFF, x5e[0], x5e[1], x5o[0], x5o[1]); sts128(w5 + X5_OFF + XH5, x5e[2], x5e[3], x5o[2], x5o[3]);
    sts128(w5 + X3_OFF, x3e[0], x3e[1], x3o[0], x3o[1]); sts128(w5 + X3_OFF + XH5, x3e[2], x3e[3], x3o[2], x3o[3]);
    if (FULL) {
        sts128(w5 + XV_OFF, xve[0], xve[1], x7e[0], x7e[1]); sts128(w5 + XV_OFF + XH9, xve[2], xve[3], x7e[2], x7e[3]);
        sts128(w5 - 16 + X9_OFF + XH9, x9e[0], x9e[1], x9o[0], x9o[1]);
        sts128(w5 - 16 + X7_OFF + XH9, x7e[0], x7e[1], x7o[0], x7o[1]);
        if (lam < 63) {
            sts128(w5 + X9_OFF, x9e[2], x9e[3], x9o[2], x9o[3]);
            sts128(w5 + X7_OFF, x7e[2], x7e[3], x7o[2], x7o[3]);
        }
    }
}

__device__ __forceinline__ void wgen(uint32_t U, uint32_t W, int lane)
{
    wgen_pass<true>(U, W, lane, lane);
    wgen_pass<true>(U, W, lane + 32, lane);
    wgen_pass<false>(U, W, lane + 64, lane);
    if (lane == 0) {
        const uint32_t e0 = lds32(U), o0 = lds32(U + 128);
        const uint32_t s0 = badd2(e0, o0);
        const uint32_t a = e0 << 16, b = s0 << 16;
        const uint32_t c = badd2(b, __byte_perm(s0, e0, 0x7610));
        const uint32_t d = badd2(b, s0);
        sts128(W + X5_OFF + XH5, 0u, a, 0u, b);
        sts128(W + XV_OFF + XH9, 0u, a, 0u, b);
        sts128(W + X9_OFF, 0u, __byte_perm(e0, c, 0x7610), 0u, d);
        sts128(W + X7_OFF, 0u, b, 0u, __byte_perm(e0, c, 0x7610));
        sts128(W + X5_OFF, 0u, 0u, 0u, 0u);
        sts128(W + XV_OFF, 0u, 0u, 0u, 0u);
    }
}

__global__ void __launch_bounds__(64 * NS, 1)
ssm_kernel(const __nv_bfloat16* __restrict__ u, const __nv_bfloat16* __restrict__ A_re, const __nv_bfloat16* __restrict__ A_im,
           const __nv_bfloat16* __restrict__ B_re, const __nv_bfloat16* __restrict__ B_im, const __nv_bfloat16* __restrict__ C_re,
           const __nv_bfloat16* __restrict__ C_im, const __nv_bfloat16* __restrict__ log_dt, const __nv_bfloat16* __restrict__ Dsk,
           __nv_bfloat16* __restrict__ out)
{
    extern __shared__ __align__(128) unsigned char smem[];
    const uint32_t sb = smem_u32(smem);
    const int tid = threadIdx.x, lane = tid & 31;
    const int w = __shfl_sync(0xffffffffu, tid >> 5, 0);
    uint32_t rank; asm("mov.u32 %0, %%cluster_ctarank;" : "=r"(rank));
    const int chbase = (blockIdx.x / CL) * GCH;
    const int slot = (w < NS) ? w : w - NS, h = (w < NS) ? 0 : 1;
    const int ch = chbase + 32 * (slot >> 1) + 8 * ((rank >> 1) & 3) + 4 * (slot & 1) + 2 * (rank >> 3) + (rank & 1);
    const int g = lane >> 2, q = lane & 3;

    TLG(15); TL(0);
    uint32_t pv[6], ldtb, dbits;
    {
        const int o = ch * N_ + 64 * h + 2 * lane;
        ldtb = __ldg(reinterpret_cast<const unsigned short*>(log_dt + ch));
        pv[0] = __ldg(reinterpret_cast<const uint32_t*>(A_re + o));
        pv[1] = __ldg(reinterpret_cast<const uint32_t*>(A_im + o));
        pv[2] = __ldg(reinterpret_cast<const uint32_t*>(B_re + o));
        pv[3] = __ldg(reinterpret_cast<const uint32_t*>(B_im + o));
        pv[4] = __ldg(reinterpret_cast<const uint32_t*>(C_re + o));
        pv[5] = __ldg(reinterpret_cast<const uint32_t*>(C_im + o));
        dbits = __ldg(reinterpret_cast<const unsigned short*>(Dsk + ch));
    }
    const int grp = slot >> 1, wi = (slot - 2) + 4 * h;
    uint4 ur[6];
    if (grp > 0) {
        const uint4* p = reinterpret_cast<const uint4*>(u + (size_t)(RPC * rank + 16 * wi + 2 * g) * D_ + chbase + 8 * q);
        #pragma unroll
        for (int k = 0; k < 6; k++) ur[k] = __ldg(p + (k / 3) * (D_ / 8) + (k % 3) * 4);
    }
    if (tid == 0) {
        mbar_init(sb + MB_U, 1);
        mbar_init(sb + MB_Y, 1); mbar_init(sb + MB_Y + 8, 1); mbar_init(sb + MB_Y + 16, 1);
        asm volatile("fence.mbarrier_init.release.cluster;" ::: "memory");
        mbar_arrive_tx(sb + MB_U, NS * 4096);
        mbar_arrive_tx(sb + MB_Y, 32 * RPC * 2); mbar_arrive_tx(sb + MB_Y + 8, 32 * RPC * 2); mbar_arrive_tx(sb + MB_Y + 16, 32 * RPC * 2);
    }
    cl_arrive();
    const uint32_t U = sb + 2 * NP + slot * 256, W = sb + UB_SIZE + slot * SLOT, KS = W + W_SIZE;
    sts128(sb + (h ? NP : 0) + (lane >> 4) * HB + slot * 256 + (lane & 15) * 16, 0u, 0u, 0u, 0u);
    TL(1);
    if (grp > 0) {
        const int mj = lane >> 3, mi = lane & 7;
        const uint32_t a = sb + YIN_OFF + (8 * (mj & 1) + mi) * YP + (mj >> 1) * 256 + wi * 16;
        #pragma unroll
        for (int k = 0; k < 6; k++) stsm4t(a + (k % 3) * 512 + (k / 3) * 128, ur[k].x, ur[k].y, ur[k].z, ur[k].w);
        asm volatile("fence.proxy.async.shared::cta;" ::: "memory");
        if (w != 11) asm volatile("bar.arrive 13, 256;" ::: "memory");
        else {
            asm volatile("bar.sync 13, 256;" ::: "memory");
            cl_wait();
            if (lane == 0) {
                const uint32_t dst = sb + (2 + (rank >> 1)) * NP + (rank & 1) * HB;
                #pragma unroll
                for (int r = 0; r < CL; r++) bulk_s2c(mapa(dst, r), sb + YIN_OFF + r * YP, NS * 256, mapa(sb + MB_U, r));
            }
            __syncwarp();
        }
        TL(2);
        if (grp == 1) asm volatile("bar.sync 14, 256;" ::: "memory");
        else asm volatile("bar.sync 15, 256;" ::: "memory");
    }
    TL(13);
    const uint32_t S = h ? W : KS;
    float isc, gmax;
    prep(S, lane, pv, ldtb, isc, gmax, grp);
    TL(3);
    float acc[2][3][4];
    kmma(S, lane, isc, gmax, acc);
    TL(4);
    const int idX = 1 + 2 * slot, idY = 2 + 2 * slot;
    if (h == 0) {
        sts128(KS + XK + lane * 16, __float_as_uint(acc[0][1][1]), __float_as_uint(acc[0][1][3]), __float_as_uint(acc[1][1][1]), __float_as_uint(acc[1][1][3]));
        sts128(KS + XK + 512 + lane * 16, __float_as_uint(acc[0][2][0]), __float_as_uint(acc[0][2][2]), __float_as_uint(acc[1][2][0]), __float_as_uint(acc[1][2][2]));
        if (lane == 0) sts32f(KS + XK + 1024, acc[0][2][1]);
        nb_sync(idX);
        const uint4 t0 = lds128(KS + XW + lane * 16), t1 = lds128(KS + XW + 512 + lane * 16), t2 = lds128(KS + XW + 1024 + lane * 16);
        const float k512 = shf(acc[0][1][1], 0) + lds32f(KS + XW + 1536);
        float fe[4], fo[4], fu[4];
        fe[0] = acc[0][0][0] + __uint_as_float(t0.x); fe[1] = acc[0][0][2] + __uint_as_float(t0.y);
        fe[2] = acc[1][0][0] + __uint_as_float(t0.z); fe[3] = acc[1][0][2] + __uint_as_float(t0.w);
        fo[0] = acc[0][0][1] + __uint_as_float(t1.x); fo[1] = acc[0][0][3] + __uint_as_float(t1.y);
        fo[2] = acc[1][0][1] + __uint_as_float(t1.z); fo[3] = acc[1][0][3] + __uint_as_float(t1.w);
        fu[0] = acc[0][1][0] + __uint_as_float(t2.x); fu[1] = acc[0][1][2] + __uint_as_float(t2.y);
        fu[2] = acc[1][1][0] + __uint_as_float(t2.z); fu[3] = acc[1][1][2] + __uint_as_float(t2.w);
        ktables(KS, lane, fe, fo, fu, k512);
        nb_arrive(idX);
        TL(5);
        cl_wait();
        mbar_wait(sb + MB_U, 0);
        cl_arrive();
        TL(6);
        float aP[NEK][4], aQ[NEK][4], aR[NEK][4];
        hconv<0, NEK>(U, KS, lane, dbits, aP, aQ, aR);
        TL(7);
        nb_sync(idY);
        hfinal<0, NEK>(U, KS, W, lane, aP, aQ, aR);
        asm volatile("fence.proxy.async.shared::cta;" ::: "memory");
        nb_arrive(idX);
        TL(8);
        cl_wait();
        if (lane == 0) {
            const uint32_t dst = sb + YIN_OFF + rank * YP + slot * 256;
            #pragma unroll
            for (int n = 0; n < 8; n++) bulk_s2c(mapa(dst, 2 * n), W + ST_OFF + 528 * n, 256, mapa(sb + MB_Y + 8 * grp, 2 * n));
        }
        __syncwarp();
    } else {
        sts128(KS + XW + lane * 16, __float_as_uint(acc[0][0][0]), __float_as_uint(acc[0][0][2]), __float_as_uint(acc[1][0][0]), __float_as_uint(acc[1][0][2]));
        sts128(KS + XW + 512 + lane * 16, __float_as_uint(acc[0][0][1]), __float_as_uint(acc[0][0][3]), __float_as_uint(acc[1][0][1]), __float_as_uint(acc[1][0][3]));
        sts128(KS + XW + 1024 + lane * 16, __float_as_uint(acc[0][1][0]), __float_as_uint(acc[0][1][2]), __float_as_uint(acc[1][1][0]), __float_as_uint(acc[1][1][2]));
        if (lane == 0) sts32f(KS + XW + 1536, acc[0][1][1]);
        nb_sync(idX);
        const uint4 t0 = lds128(KS + XK + lane * 16), t1 = lds128(KS + XK + 512 + lane * 16);
        const float k2048 = acc[0][2][1] + lds32f(KS + XK + 1024);
        float v2[4], v3[4];
        v2[0] = acc[0][1][1] + __uint_as_float(t0.x); v2[1] = acc[0][1][3] + __uint_as_float(t0.y);
        v2[2] = acc[1][1][1] + __uint_as_float(t0.z); v2[3] = acc[1][1][3] + __uint_as_float(t0.w);
        v3[0] = acc[0][2][0] + __uint_as_float(t1.x); v3[1] = acc[0][2][2] + __uint_as_float(t1.y);
        v3[2] = acc[1][2][0] + __uint_as_float(t1.z); v3[3] = acc[1][2][2] + __uint_as_float(t1.w);
        wtables(KS, lane, v2, v3, k2048);
        TL(5);
        if (w != 11) cl_wait();
        mbar_wait(sb + MB_U, 0);
        cl_arrive();
        TL(6);
        wgen(U, W, lane);
        __syncwarp();
        s23(W, KS, lane);
        nb_sync(idX);
        nb_arrive(idY);
        TL(7);
        float aP[8 - NEK][4], aQ[8 - NEK][4], aR[8 - NEK][4];
        hconv<NEK, 8 - NEK>(U, KS, lane, dbits, aP, aQ, aR);
        hfinal<NEK, 8 - NEK>(U, KS, W, lane, aP, aQ, aR);
        asm volatile("fence.proxy.async.shared::cta;" ::: "memory");
        nb_sync(idX);
        TL(8);
        cl_wait();
        if (lane == 0) {
            const uint32_t dst = sb + YIN_OFF + rank * YP + slot * 256;
            #pragma unroll
            for (int n = 0; n < 8; n++) bulk_s2c(mapa(dst, 2 * n + 1), W + ST_OFF + 528 * n + 256, 256, mapa(sb + MB_Y + 8 * grp, 2 * n + 1));
        }
        __syncwarp();
    }
    {
        TL(9);
        mbar_wait(sb + MB_Y + 8 * grp, 0);
        cl_arrive();
        TL(10);
        const int mj = lane >> 3, mi = lane & 7;
        const int ocg = grp, rg0 = ((slot & 1) + 2 * h) * 4;
        const uint32_t ya = sb + YIN_OFF + (8 * (mj & 1) + mi) * YP + (2 * ocg + (mj >> 1)) * 256 + rg0 * 16;
        __nv_bfloat16* op = out + (size_t)(RPC * rank + 8 * rg0 + g) * D_ + chbase + 32 * ocg + 8 * q;
        #pragma unroll
        for (int i = 0; i < 4; i++) {
            uint32_t y0, y1, y2, y3;
            ldsm4t(y0, y1, y2, y3, ya + i * 16);
            asm volatile("st.global.v4.u32 [%0], {%1,%2,%3,%4};" ::"l"(op + (size_t)i * 8 * D_), "r"(y0), "r"(y1), "r"(y2), "r"(y3) : "memory");
        }
    }
    TL(11);
    cl_wait();
    TL(12); TLG(14);
}

__device__ float g_kscr[D_ * L_];
__global__ void fb_kgen(const __nv_bfloat16* __restrict__ A_re, const __nv_bfloat16* __restrict__ A_im, const __nv_bfloat16* __restrict__ B_re,
                        const __nv_bfloat16* __restrict__ B_im, const __nv_bfloat16* __restrict__ C_re, const __nv_bfloat16* __restrict__ C_im,
                        const __nv_bfloat16* __restrict__ log_dt)
{
    const int d = blockIdx.y, l = blockIdx.x * blockDim.x + threadIdx.x;
    const float dt = __bfloat162float(__float2bfloat16_rn(expf(__bfloat162float(log_dt[d]))));
    const float lf = __bfloat162float(__float2bfloat16_rn((float)l));
    float acc = 0.f;
    for (int n = 0; n < N_; n++) {
        const int o = d * N_ + n;
        const float zr = dt * __bfloat162float(A_re[o]), zi = dt * __bfloat162float(A_im[o]);
        const float br = dt * __bfloat162float(B_re[o]), bi = dt * __bfloat162float(B_im[o]);
        const float cr = __bfloat162float(C_re[o]), ci = __bfloat162float(C_im[o]);
        float sn, cs; sincosf(zi * lf, &sn, &cs);
        const float m = expf(zr * lf);
        acc += m * ((cr * br - ci * bi) * cs - (cr * bi + ci * br) * sn);
    }
    g_kscr[d * L_ + l] = acc;
}
__global__ void fb_conv(const __nv_bfloat16* __restrict__ u, const __nv_bfloat16* __restrict__ Dsk, __nv_bfloat16* __restrict__ out)
{
    const int d = blockIdx.y * blockDim.x + threadIdx.x, t = blockIdx.x;
    float y = 0.f;
    for (int l = 0; l <= t; l++) y = fmaf(g_kscr[d * L_ + l], __bfloat162float(u[(size_t)(t - l) * D_ + d]), y);
    const float sk = __bfloat162float(__float2bfloat16_rn(__bfloat162float(u[(size_t)t * D_ + d]) * __bfloat162float(Dsk[d])));
    out[(size_t)t * D_ + d] = __float2bfloat16_rn(__bfloat162float(__float2bfloat16_rn(y)) + sk);
}

}

extern "C" void kernel_launch(void* const* d_in, const int* in_sizes, int n_in, void* d_out, int out_size)
{
    static int mode = -1;
    static cudaLaunchConfig_t cfg;
    static cudaLaunchAttribute at[1];
    if (mode < 0) {
        mode = 1;
        if (cudaFuncSetAttribute(ssm_kernel, cudaFuncAttributeMaxDynamicSharedMemorySize, SMEM_BYTES) == cudaSuccess &&
            cudaFuncSetAttribute(ssm_kernel, cudaFuncAttributeNonPortableClusterSizeAllowed, 1) == cudaSuccess) {
            cfg = cudaLaunchConfig_t{};
            cfg.gridDim = dim3((D_ / GCH) * CL); cfg.blockDim = dim3(64 * NS); cfg.dynamicSmemBytes = SMEM_BYTES; cfg.stream = cudaStreamPerThread;
            at[0].id = cudaLaunchAttributeClusterDimension;
            at[0].val.clusterDim.x = CL; at[0].val.clusterDim.y = 1; at[0].val.clusterDim.z = 1;
            cfg.attrs = at; cfg.numAttrs = 1;
            int nc = 0;
            if (cudaOccupancyMaxActiveClusters(&nc, ssm_kernel, &cfg) == cudaSuccess && nc >= 1) mode = 0;
        }
        cudaGetLastError();
    }
    const __nv_bfloat16* p[9];
    for (int i = 0; i < 9; i++) p[i] = (const __nv_bfloat16*)d_in[i];
    if (mode == 0)
        cudaLaunchKernelEx(&cfg, ssm_kernel, p[0], p[1], p[2], p[3], p[4], p[5], p[6], p[7], p[8], (__nv_bfloat16*)d_out);
    else {
        fb_kgen<<<dim3(L_ / 256, D_), 256, 0, cudaStreamPerThread>>>(p[1], p[2], p[3], p[4], p[5], p[6], p[7]);
        fb_conv<<<dim3(L_, D_ / 192), 192, 0, cudaStreamPerThread>>>(p[0], p[8], (__nv_bfloat16*)d_out);
    }
}
```

```cpp
#include <cuda_runtime.h>
#include <cuda_bf16.h>
#include <cuda_fp16.h>
#include <stdint.h>

namespace {

constexpr int L_ = 2048, D_ = 576, N_ = 128;

constexpr int CL = 8, GCH = 40, NS = 5, RPC = 256, NCL = (D_ + GCH - 1) / GCH;
constexpr int HB = NS * 256, NP = 2 * HB + 16, UB_SIZE = (10 * NP + 127) / 128 * 128;
constexpr int X5_OFF = 0, XH5 = 1600, X3_OFF = 3200, X9_OFF = 6400, XH9 = 1088, X7_OFF = 8512, XV_OFF = 10624, W_SIZE = 12800;
constexpr int KS_SIZE = 16256;
constexpr int SLOT = W_SIZE + KS_SIZE;
constexpr int YP = 2 * HB + 16;
constexpr int YIN_OFF = UB_SIZE + NS * SLOT;
constexpr int MB_U = YIN_OFF + CL * YP, MB_Y = MB_U + 8;
constexpr int SMEM_BYTES = MB_U + 64;
constexpr int KG_SEED = 21, KG_FAC = 37 * 256;
constexpr int T4E = 0;
constexpr int T4Q = 4352;
constexpr int T4R = 6912;
constexpr int PQ = 9472;
constexpr int PR = 10048;
constexpr int XW = 10624;
constexpr int XK = 12192;
constexpr int P2E = 13136;
constexpr int P2O = 13928;
constexpr int PT3 = 14720;
constexpr int TSC = 16208;
constexpr int P2_OFF = 0, P2_PITCH = 1040, ST_OFF = 6528;
#define NEK_ 6
constexpr int NEK = NEK_;

__device__ __forceinline__ uint32_t smem_u32(const void* p) { return (uint32_t)__cvta_generic_to_shared(p); }
__device__ __forceinline__ uint32_t mapa(uint32_t addr, uint32_t rank) {
    uint32_t r; asm volatile("mapa.shared::cluster.u32 %0, %1, %2;" : "=r"(r) : "r"(addr), "r"(rank)); return r;
}
__device__ __forceinline__ void mbar_init(uint32_t bar, uint32_t cnt) {
    asm volatile("mbarrier.init.shared::cta.b64 [%0], %1;" ::"r"(bar), "r"(cnt) : "memory");
}
__device__ __forceinline__ void mbar_arrive_tx(uint32_t bar, uint32_t bytes) {
    asm volatile("mbarrier.arrive.expect_tx.shared::cta.b64 _, [%0], %1;" ::"r"(bar), "r"(bytes) : "memory");
}
__device__ __forceinline__ void mbar_wait(uint32_t bar, uint32_t parity) {
    uint32_t ok; int it = 0;
    do {
        asm volatile("{\n.reg .pred p;\nmbarrier.try_wait.parity.shared::cta.b64 p, [%1], %2;\nselp.u32 %0, 1, 0, p;\n}"
                     : "=r"(ok) : "r"(bar), "r"(parity) : "memory");
        if (++it > (1 << 22)) __trap();
    } while (!ok);
}
__device__ __forceinline__ void nb_sync(int id) { asm volatile("bar.sync %0, 64;" ::"r"(id) : "memory"); }
__device__ __forceinline__ void nb_arrive(int id) { asm volatile("bar.arrive %0, 64;" ::"r"(id) : "memory"); }
__device__ __forceinline__ void cta_sync13() { asm volatile("bar.sync 13, 384;" ::: "memory"); }
__device__ __forceinline__ void cta_arrive13() { asm volatile("bar.arrive 13, 384;" ::: "memory"); }
__device__ __forceinline__ void ldsm4(uint32_t& r0, uint32_t& r1, uint32_t& r2, uint32_t& r3, uint32_t a) {
    asm volatile("ldmatrix.sync.aligned.m8n8.x4.shared.b16 {%0,%1,%2,%3}, [%4];" : "=r"(r0), "=r"(r1), "=r"(r2), "=r"(r3) : "r"(a) : "memory");
}
__device__ __forceinline__ void ldsm4t(uint32_t& r0, uint32_t& r1, uint32_t& r2, uint32_t& r3, uint32_t a) {
    asm volatile("ldmatrix.sync.aligned.m8n8.x4.trans.shared.b16 {%0,%1,%2,%3}, [%4];" : "=r"(r0), "=r"(r1), "=r"(r2), "=r"(r3) : "r"(a) : "memory");
}
__device__ __forceinline__ void ldsm2t(uint32_t& r0, uint32_t& r1, uint32_t a) {
    asm volatile("ldmatrix.sync.aligned.m8n8.x2.trans.shared.b16 {%0,%1}, [%2];" : "=r"(r0), "=r"(r1) : "r"(a) : "memory");
}
__device__ __forceinline__ void mma_bf16(float* c, uint32_t a0, uint32_t a1, uint32_t a2, uint32_t a3, uint32_t b0, uint32_t b1) {
    asm volatile("mma.sync.aligned.m16n8k16.row.col.f32.bf16.bf16.f32 {%0,%1,%2,%3},{%4,%5,%6,%7},{%8,%9},{%0,%1,%2,%3};"
                 : "+f"(c[0]), "+f"(c[1]), "+f"(c[2]), "+f"(c[3]) : "r"(a0), "r"(a1), "r"(a2), "r"(a3), "r"(b0), "r"(b1));
}
__device__ __forceinline__ void mma_sp(float* c, uint32_t a0, uint32_t a1, uint32_t a2, uint32_t a3, uint32_t b0, uint32_t b1, uint32_t b2, uint32_t b3, uint32_t e) {
    asm volatile("mma.sp::ordered_metadata.sync.aligned.m16n8k32.row.col.f32.bf16.bf16.f32 {%0,%1,%2,%3},{%4,%5,%6,%7},{%8,%9,%10,%11},{%0,%1,%2,%3},%12,0x0;"
                 : "+f"(c[0]), "+f"(c[1]), "+f"(c[2]), "+f"(c[3]) : "r"(a0), "r"(a1), "r"(a2), "r"(a3), "r"(b0), "r"(b1), "r"(b2), "r"(b3), "r"(e));
}
__device__ __forceinline__ void mma_f16(float* c, uint32_t a0, uint32_t a1, uint32_t a2, uint32_t a3, uint32_t b0, uint32_t b1) {
    asm volatile("mma.sync.aligned.m16n8k16.row.col.f32.f16.f16.f32 {%0,%1,%2,%3},{%4,%5,%6,%7},{%8,%9},{%0,%1,%2,%3};"
                 : "+f"(c[0]), "+f"(c[1]), "+f"(c[2]), "+f"(c[3]) : "r"(a0), "r"(a1), "r"(a2), "r"(a3), "r"(b0), "r"(b1));
}
__device__ __forceinline__ uint32_t lds32(uint32_t a) { uint32_t v; asm volatile("ld.shared.u32 %0, [%1];" : "=r"(v) : "r"(a) : "memory"); return v; }
__device__ __forceinline__ float lds32f(uint32_t a) { float v; asm volatile("ld.shared.f32 %0, [%1];" : "=f"(v) : "r"(a) : "memory"); return v; }
__device__ __forceinline__ float2 lds64f(uint32_t a) { float2 v; asm volatile("ld.shared.v2.f32 {%0,%1}, [%2];" : "=f"(v.x), "=f"(v.y) : "r"(a) : "memory"); return v; }
__device__ __forceinline__ uint2 lds64(uint32_t a) { uint2 v; asm volatile("ld.shared.v2.u32 {%0,%1}, [%2];" : "=r"(v.x), "=r"(v.y) : "r"(a) : "memory"); return v; }
__device__ __forceinline__ uint4 lds128(uint32_t a) { uint4 v; asm volatile("ld.shared.v4.u32 {%0,%1,%2,%3}, [%4];" : "=r"(v.x), "=r"(v.y), "=r"(v.z), "=r"(v.w) : "r"(a) : "memory"); return v; }
__device__ __forceinline__ void sts16(uint32_t a, uint16_t v) { asm volatile("st.shared.u16 [%0], %1;" ::"r"(a), "h"(v) : "memory"); }
__device__ __forceinline__ void sts32(uint32_t a, uint32_t v) { asm volatile("st.shared.u32 [%0], %1;" ::"r"(a), "r"(v) : "memory"); }
__device__ __forceinline__ void sts32f(uint32_t a, float v) { asm volatile("st.shared.f32 [%0], %1;" ::"r"(a), "f"(v) : "memory"); }
__device__ __forceinline__ void sts64(uint32_t a, uint32_t x, uint32_t y) { asm volatile("st.shared.v2.u32 [%0], {%1,%2};" ::"r"(a), "r"(x), "r"(y) : "memory"); }
__device__ __forceinline__ void sts64f(uint32_t a, float x, float y) { asm volatile("st.shared.v2.f32 [%0], {%1,%2};" ::"r"(a), "f"(x), "f"(y) : "memory"); }
__device__ __forceinline__ void sts128(uint32_t a, uint32_t x, uint32_t y, uint32_t z, uint32_t w) { asm volatile("st.shared.v4.u32 [%0], {%1,%2,%3,%4};" ::"r"(a), "r"(x), "r"(y), "r"(z), "r"(w) : "memory"); }

__device__ __forceinline__ uint32_t pack_bf16(float lo, float hi) {
    uint32_t r; asm("cvt.rn.bf16x2.f32 %0, %1, %2;" : "=r"(r) : "f"(hi), "f"(lo)); return r;
}
__device__ __forceinline__ uint16_t cvt_bf16(float v) { uint16_t r; asm("cvt.rn.bf16.f32 %0, %1;" : "=h"(r) : "f"(v)); return r; }
__device__ __forceinline__ uint32_t pack_f16(float lo, float hi) {
    uint32_t r; asm("cvt.rn.f16x2.f32 %0, %1, %2;" : "=r"(r) : "f"(hi), "f"(lo)); return r;
}
__device__ __forceinline__ uint32_t badd2(uint32_t a, uint32_t b) {
    __nv_bfloat162 r = __hadd2_rn(*reinterpret_cast<__nv_bfloat162*>(&a), *reinterpret_cast<__nv_bfloat162*>(&b));
    return *reinterpret_cast<uint32_t*>(&r);
}
__device__ __forceinline__ uint32_t bmul2(uint32_t a, uint32_t b) {
    __nv_bfloat162 r = __hmul2_rn(*reinterpret_cast<__nv_bfloat162*>(&a), *reinterpret_cast<__nv_bfloat162*>(&b));
    return *reinterpret_cast<uint32_t*>(&r);
}
__device__ __forceinline__ uint32_t shift1(uint32_t a, uint32_t b) { return __byte_perm(a, b, 0x5432); }

__device__ __forceinline__ float shf(float v, int src) { return __shfl_sync(0xffffffffu, v, src); }
__device__ __forceinline__ uint32_t shu(uint32_t v, int src) { return __shfl_sync(0xffffffffu, v, src); }
__device__ __forceinline__ void stsm4t(uint32_t a, uint32_t r0, uint32_t r1, uint32_t r2, uint32_t r3) {
    asm volatile("stmatrix.sync.aligned.m8n8.x4.trans.shared.b16 [%0], {%1,%2,%3,%4};" ::"r"(a), "r"(r0), "r"(r1), "r"(r2), "r"(r3) : "memory");
}
__device__ __forceinline__ void bulk_s2c(uint32_t dst, uint32_t src, uint32_t bytes, uint32_t mb) {
    asm volatile("cp.async.bulk.shared::cluster.shared::cta.mbarrier::complete_tx::bytes [%0], [%1], %2, [%3];"
                 ::"r"(dst), "r"(src), "r"(bytes), "r"(mb) : "memory");
}
__device__ __forceinline__ void cl_arrive() { asm volatile("barrier.cluster.arrive.relaxed.aligned;" ::: "memory"); }
__device__ __forceinline__ void cl_wait() { asm volatile("barrier.cluster.wait.acquire.aligned;" ::: "memory"); }

__device__ __forceinline__ bool elect_one() {
    uint32_t p; asm volatile("{\n.reg .pred p;\nelect.sync _|p, 0xffffffff;\nselp.u32 %0, 1, 0, p;\n}" : "=r"(p)); return p != 0;
}

struct H2C { __half2 r, i; };
__device__ __forceinline__ H2C hc_mul(const H2C& a, const H2C& b) {
    H2C o;
    o.r = __hfma2(a.r, b.r, __hneg2(__hmul2(a.i, b.i)));
    o.i = __hfma2(a.r, b.i, __hmul2(a.i, b.r));
    return o;
}
__device__ __forceinline__ H2C hc_mulc(const H2C& a, const H2C& e) {
    H2C o;
    o.r = __hfma2(a.r, e.r, __hmul2(a.i, e.i));
    o.i = __hfma2(a.i, e.r, __hneg2(__hmul2(a.r, e.i)));
    return o;
}
__device__ __forceinline__ uint32_t h2u(__half2 h) { return *reinterpret_cast<uint32_t*>(&h); }
__device__ __forceinline__ __half2 u2h(uint32_t u) { return *reinterpret_cast<__half2*>(&u); }
__device__ __forceinline__ float2 csq(float2 a) { return make_float2(fmaf(a.x, a.x, -a.y * a.y), (a.x + a.x) * a.y); }
__device__ __forceinline__ H2C hpack(float2 a, float2 b) { H2C o; o.r = u2h(pack_f16(a.x, b.x)); o.i = u2h(pack_f16(a.y, b.y)); return o; }
__device__ __forceinline__ float ex2f(float x) { float r; asm("ex2.approx.ftz.f32 %0, %1;" : "=f"(r) : "f"(x)); return r; }
__device__ __forceinline__ float bf_lo(uint32_t v) { return __uint_as_float(v << 16); }
__device__ __forceinline__ float bf_hi(uint32_t v) { return __uint_as_float(v & 0xffff0000u); }

#define TL(i)
#define TLG(i)

__device__ __forceinline__ void exp_pair(float zr2  , float ph, float pl, float mult, float2& E) {
    float p = ph * mult;
    float r = (p - rintf(p)) + pl * mult;
    float ang = r * 6.283185307179586f;
    float m = ex2f(zr2 * mult);
    E.x = m * __cosf(ang);
    E.y = m * __sinf(ang);
}

__device__ __forceinline__ void prep(uint32_t S, int lane, const uint32_t* __restrict__ pv, uint32_t ldtb, float& isc, float& gmaxo)
{
    float dt;
    {
        const float ldt = __uint_as_float(ldtb << 16);
        float e = expf(ldt);
        uint32_t b = __float_as_uint(e);
        int low = (int)(b & 0xffffu) - 0x8000;
        if (low >= -4 && low <= 4) e = (float)exp((double)ldt);
        dt = __bfloat162float(__float2bfloat16_rn(e));
    }
    float zr[2], zi[2]; float2 cb[2];
    #pragma unroll
    for (int k = 0; k < 2; k++) {
        float are = k ? bf_hi(pv[0]) : bf_lo(pv[0]);
        float aim = k ? bf_hi(pv[1]) : bf_lo(pv[1]);
        float bre = k ? bf_hi(pv[2]) : bf_lo(pv[2]);
        float bim = k ? bf_hi(pv[3]) : bf_lo(pv[3]);
        float cre = k ? bf_hi(pv[4]) : bf_lo(pv[4]);
        float cim = k ? bf_hi(pv[5]) : bf_lo(pv[5]);
        zr[k] = dt * are; zi[k] = dt * aim;
        float dbr = dt * bre, dbi = dt * bim;
        cb[k].x = fmaf(cre, dbr, -cim * dbi);
        cb[k].y = fmaf(cre, dbi, cim * dbr);
    }
    float gmax = fmaxf(fmaxf(zr[0], zr[1]), 0.f);
    float cmax = fmaxf(fmaxf(fabsf(cb[0].x), fabsf(cb[0].y)), fmaxf(fabsf(cb[1].x), fabsf(cb[1].y)));
    gmax = __uint_as_float(__reduce_max_sync(0xffffffffu, __float_as_uint(gmax)));
    int ex = (int)(__reduce_max_sync(0xffffffffu, __float_as_uint(cmax)) >> 23);
    ex = min(max(ex, 30), 230);
    const float sc = __uint_as_float((uint32_t)(127 + 10 + 127 - ex) << 23);
    isc = __uint_as_float((uint32_t)(ex - 10) << 23);
    gmaxo = gmax;

    float2 E1[2], E256[2];
    #pragma unroll
    for (int k = 0; k < 2; k++) {
        const float C1 = 0.15915494309189535f;
        const float C2 = (float)(0.15915494309189533576888 - (double)0.15915494309189535f);
        float ph = zi[k] * C1;
        float pl = fmaf(zi[k], C1, -ph) + zi[k] * C2;
        float z2 = (zr[k] - gmax) * 1.4426950408889634f;
        exp_pair(z2, ph, pl, 1.f, E1[k]);
        exp_pair(z2, ph, pl, 256.f, E256[k]);
    }
    const uint32_t wr = S + lane * 4;
    auto put = [&](int row, const H2C& v) {
        const uint32_t a = (wr ^ ((row & 7) << 4)) + row * 256;
        sts32(a, h2u(v.r)); sts32(a + 128, h2u(v.i));
    };
    float2 a[2];
    H2C h1 = hpack(E1[0], E1[1]);
    a[0] = csq(E1[0]); a[1] = csq(E1[1]); H2C h2 = hpack(a[0], a[1]);
    a[0] = csq(a[0]); a[1] = csq(a[1]); H2C h4 = hpack(a[0], a[1]);
    a[0] = csq(a[0]); a[1] = csq(a[1]); H2C h8 = hpack(a[0], a[1]);
    a[0] = csq(a[0]); a[1] = csq(a[1]); H2C h16 = hpack(a[0], a[1]);
    a[0] = csq(a[0]); a[1] = csq(a[1]); H2C h32 = hpack(a[0], a[1]);
    a[0] = csq(a[0]); a[1] = csq(a[1]); H2C h64 = hpack(a[0], a[1]);
    a[0] = csq(a[0]); a[1] = csq(a[1]); H2C h128 = hpack(a[0], a[1]);
    {
        float2 c0 = make_float2(cb[0].x * sc, -cb[0].y * sc), c1 = make_float2(cb[1].x * sc, -cb[1].y * sc);
        H2C s[4];
        s[0] = hpack(c0, c1);
        s[1] = hc_mulc(s[0], h8); s[2] = hc_mulc(s[0], h16); s[3] = hc_mulc(s[1], h16);
        #pragma unroll
        for (int k = 0; k < 4; k++) {
            const int row = KG_SEED + (k & 1) + 8 * (k >> 1);
            H2C t1 = hc_mulc(s[k], h64), t2 = hc_mulc(s[k], h128);
            put(row, s[k]); put(row + 2, t1); put(row + 4, t2); put(row + 6, hc_mulc(t1, h128));
        }
    }
    sts64(S + KG_FAC + lane * 8, h2u(h32.r), h2u(h32.i));
    { H2C h0; h0.r = u2h(0x3c003c00u); h0.i = u2h(0u); put(0, h0); }
    put(1, h1); put(2, h2); put(4, h4);
    H2C h3 = hc_mul(h1, h2); put(3, h3);
    put(5, hc_mul(h4, h1));
    H2C h6 = hc_mul(h4, h2); put(6, h6);
    put(7, hc_mul(h4, h3));
    H2C h256 = hpack(E256[0], E256[1]);
    put(8, h256); put(10, hc_mul(h256, h2)); put(12, hc_mul(h256, h4)); put(14, hc_mul(h256, h6));
    a[0] = csq(E256[0]); a[1] = csq(E256[1]); H2C h512 = hpack(a[0], a[1]);
    H2C h768 = hc_mul(h512, h256);
    put(9, h512); put(11, hc_mul(h512, h4)); put(13, h768); put(15, hc_mul(h768, h4));
    a[0] = csq(a[0]); a[1] = csq(a[1]); H2C h1024 = hpack(a[0], a[1]);
    put(16, h1024); put(17, hc_mul(h1024, h256)); put(18, hc_mul(h1024, h512)); put(19, hc_mul(h1024, h768));
    a[0] = csq(a[0]); a[1] = csq(a[1]); put(20, hpack(a[0], a[1]));
}

__device__ __forceinline__ void kmma(uint32_t S, int lane, float isc, float gmax, float (&acc)[2][3][4])
{
    const int q = lane & 3;
    #pragma unroll
    for (int i = 0; i < 2; i++)
        #pragma unroll
        for (int j = 0; j < 3; j++)
            #pragma unroll
            for (int k = 0; k < 4; k++) acc[i][j][k] = 0.f;
    const int mi = lane >> 3, r = lane & 7;
    const int rowA = KG_SEED + (mi & 1) * 8 + r;
    const int row2 = (r == 1) ? 20 : 16 + (r >> 1);
    const uint32_t aA = S + rowA * 256 + (mi >> 1) * 128 + ((rowA & 7) << 4);
    const uint32_t aB = S + ((mi >> 1) * 8 + r) * 256 + (mi & 1) * 128 + (r << 4);
    const uint32_t aC = (S + row2 * 256 + (mi & 1) * 128 + ((row2 & 7) << 4)) ^ ((mi >> 1) << 4);
    const uint32_t aF = S + KG_FAC + q * 8;
    #pragma unroll
    for (int ks = 0; ks < 8; ks += 2) {
        uint32_t c[4];
        ldsm4(c[0], c[1], c[2], c[3], aC ^ (ks << 4));
        #pragma unroll
        for (int k2 = 0; k2 < 2; k2++) {
            uint32_t a0, a1, a2, a3, b00, b01, b10, b11;
            ldsm4(a0, a1, a2, a3, aA ^ ((ks + k2) << 4));
            ldsm4(b00, b01, b10, b11, aB ^ ((ks + k2) << 4));
            const uint2 f0 = lds64(aF + (ks + k2) * 32);
            H2C f; f.r = u2h(f0.x); f.i = u2h(f0.y);
            H2C s0; s0.r = u2h(a0); s0.i = u2h(a2);
            H2C s1; s1.r = u2h(a1); s1.i = u2h(a3);
            const H2C t0 = hc_mulc(s0, f), t1 = hc_mulc(s1, f);
            mma_f16(acc[0][0], a0, a1, a2, a3, b00, b01);
            mma_f16(acc[0][1], a0, a1, a2, a3, b10, b11);
            mma_f16(acc[0][2], a0, a1, a2, a3, c[2 * k2], c[2 * k2 + 1]);
            mma_f16(acc[1][0], h2u(t0.r), h2u(t1.r), h2u(t0.i), h2u(t1.i), b00, b01);
            mma_f16(acc[1][1], h2u(t0.r), h2u(t1.r), h2u(t0.i), h2u(t1.i), b10, b11);
            mma_f16(acc[1][2], h2u(t0.r), h2u(t1.r), h2u(t0.i), h2u(t1.i), c[2 * k2], c[2 * k2 + 1]);
        }
    }
    if (gmax > 0.f) {
        const float g2 = gmax * 1.4426950408889634f;
        const int seed0 = 64 * (lane >> 3) + 8 * ((lane >> 2) & 1);
        #pragma unroll
        for (int i = 0; i < 2; i++)
            #pragma unroll
            for (int t = 0; t < 3; t++)
                #pragma unroll
                for (int k = 0; k < 4; k++) {
                    const int b = k & 1;
                    int l = seed0 + 16 * ((k >> 1) + 2 * i);
                    if (t == 0) l += 2 * q + b;
                    else if (t == 1) l += b ? (512 + 256 * (q >> 1) + 4 * (q & 1)) : (256 + 2 * q);
                    else l += b ? 2048 : (1024 + 256 * q);
                    acc[i][t][k] *= isc * exp2f(g2 * (float)l);
                }
    } else {
        #pragma unroll
        for (int i = 0; i < 2; i++)
            #pragma unroll
            for (int t = 0; t < 3; t++)
                #pragma unroll
                for (int k = 0; k < 4; k++) acc[i][t][k] *= isc;
    }
}

__device__ __forceinline__ void ktables(uint32_t KS, int lane, const float (&fe)[4], const float (&fo)[4], float (&fu)[4], float k512)
{
    const int a = lane >> 3, r = lane & 7;
    const bool r7 = (r == 7), l31 = (lane == 31);
    const int sp = (r > 0) ? lane - 1 : lane + 7;
    const int s0 = (lane + 31) & 31;
    {
        const uint32_t z = KS + (lane & 15) * 16;
        sts128((lane < 16) ? z + T4E : z + T4E + 256 * 16, 0u, 0u, 0u, 0u);
        sts128((lane < 16) ? z + T4Q : z + T4R, 0u, 0u, 0u, 0u);
        sts128(KS + PQ + lane * 16, 0u, 0u, 0u, 0u); sts128(KS + PQ + 512 + lane * 16, 0u, 0u, 0u, 0u);
        if (lane < 8) sts128(KS + PQ + 1024 + lane * 16, 0u, 0u, 0u, 0u);
    }
    if (l31) fu[3] -= k512;
    auto pred = [&](const float (&x)[4], float wrapv, float (&o)[4]) {
        o[0] = shf(r7 ? (l31 ? wrapv : x[3]) : x[0], s0);
        #pragma unroll
        for (int j = 1; j < 4; j++) o[j] = shf(r7 ? x[j - 1] : x[j], sp);
    };
    float A[4], B[4], C[4], Pu[4];
    pred(fe, 0.f, A); pred(fo, 0.f, B); pred(fu, fe[3], Pu); pred(B, 0.f, C);
    uint32_t We[4], Wq[4], Wr[4], Wu[4];
    float d[4];
    #pragma unroll
    for (int j = 0; j < 4; j++) {
        We[j] = pack_bf16(fe[j], A[j]);
        Wr[j] = pack_bf16(fo[j] - fe[j], B[j] - A[j]);
        Wq[j] = pack_bf16(B[j] - fe[j], C[j] - A[j]);
        Wu[j] = pack_bf16(fu[j], Pu[j]);
        d[j] = fu[j] - Pu[j];
    }
    uint32_t Xq[2], Xr[2];
    {
        const uint32_t D01 = pack_bf16(d[0], d[1]), D12 = pack_bf16(d[1], d[2]);
        const uint32_t Dp = shu(r7 ? (D01 << 16) : D01, sp);
        const uint32_t Dn = shu((r == 0) ? D12 : D01, (r < 7) ? lane + 1 : lane - 7);
        const bool odd = r & 1;
        const uint32_t sq = (odd ? D01 : Dp) ^ 0x80008000u, sr = odd ? Dn : D01;
        Xq[0] = odd ? (sq & 0xffffu) : (sq << 16); Xq[1] = odd ? (sq >> 16) : (sq & 0xffff0000u);
        Xr[0] = odd ? (sr & 0xffffu) : (sr << 16); Xr[1] = odd ? (sr >> 16) : (sr & 0xffff0000u);
        const float q128 = shf(fo[3], 31) - shf(fu[0], 0);
        const uint32_t q128b = cvt_bf16(q128);
        const uint32_t w3q = shu(Wq[3], 31), w3r = shu(Wr[3], 31);
        if (lane == 0) { Xq[0] = __byte_perm(q128b, w3q, 0x5410); Xr[0] = w3r << 16; }
        if (lane == 1) Xq[0] |= q128b << 16;
    }
    __syncwarp();
    {
        const int up = (lane + 8) & 31, dn = (lane + 24) & 31;
        const bool a0 = (a == 0), a3 = (a == 3);
        const uint32_t ad = KS + (lane + 24 * a + 8) * 16;
        const uint32_t eU = shu(a0 ? Wu[0] : We[0], up);
        const uint32_t eD0 = shu(We[3], dn);
        const uint32_t uU = shu(Wu[0], up), uD0 = shu(Wu[3], dn);
        const uint32_t qU = shu(a0 ? Xq[0] : Wq[0], up), qD0 = shu(Wq[3], dn);
        const uint32_t rU = shu(a0 ? Xr[0] : Wr[0], up), rD0 = shu(Wr[3], dn);
        auto quad = [&](uint32_t p, const uint32_t (&f)[4], uint32_t dnv, uint32_t upv) {
            sts128(p, f[0], f[1], dnv, f[0]);
            sts128(p + 128, f[1], f[2], f[0], f[1]);
            sts128(p + 256, f[2], f[3], f[1], f[2]);
            sts128(p + 384, f[3], upv, f[2], f[3]);
        };
        quad(ad + T4E, We, a0 ? 0u : eD0, eU);
        quad(ad + T4E + 2048, Wu, a0 ? eD0 : uD0, a3 ? 0u : uU);
        quad(ad + T4Q, Wq, a0 ? 0u : qD0, qU);
        quad(ad + T4R, Wr, a0 ? 0u : rD0, rU);
        if (a0) {
            sts32(ad + T4E - 128 + 4, We[0]); sts32(ad + T4Q - 128 + 4, Wq[0]); sts32(ad + T4R - 128 + 4, Wr[0]);
            sts128(ad + T4Q + 2048, Xq[0], Xq[1], qD0, Xq[0]);
            sts128(ad + T4R + 2048, Xr[0], Xr[1], rD0, Xr[0]);
        }
        if (a3) sts32(ad + T4E + 2048 + 512 + 8, Wu[3]);
    }
    __syncwarp();
    if (l31) {
        const uint16_t b = (uint16_t)(Wu[3] & 0xffffu);
        sts16(KS + T4E + 264 * 16 + 2, b); sts16(KS + T4E + 264 * 16 + 14, b); sts16(KS + T4E + 256 * 16 + 6, b);
        const uint16_t nb = b ^ 0x8000u;
        const uint32_t p = KS + PR + (127 - 60) * 8;
        sts16(p, nb); sts16(p - 28, nb); sts16(p + 10, nb); sts16(p - 18, nb);
    }
    {
        const uint32_t p = KS + ((r & 1) ? PQ : PR) + (4 + 16 * a + ((r - 1) >> 1)) * 8;
        const float sg = (r & 1) ? -1.f : 1.f;
        #pragma unroll
        for (int j = 0; j < 4; j++) {
            const uint16_t b = cvt_bf16(d[j] * sg);
            if (j > 0 || lane != 0) { sts16(p + 32 * j, b); sts16(p + 32 * j - 28, b); sts16(p + 32 * j + 10, b); sts16(p + 32 * j - 18, b); }
        }
    }
}

__device__ __forceinline__ void wtables(uint32_t KS, int lane, const float (&v2)[4], const float (&v3)[4], float k2048)
{
    const int a = lane >> 3, e = (lane >> 2) & 1, q = lane & 3;
    #pragma unroll
    for (int i = 0; i < 6; i++) sts128(KS + P2E + (lane + 32 * i) * 16, 0u, 0u, 0u, 0u);
    __syncwarp();
    {
        const uint32_t p = KS + ((q & 1) ? P2O : P2E) + (36 * (q >> 1) + 9 * a + e + 18) * 8;
        const uint32_t pa = p - ((q & 1) ? 68 : 0), pb = p - ((q & 1) ? 0 : 68);
        #pragma unroll
        for (int j = 0; j < 4; j++) {
            const uint16_t b = cvt_bf16(v2[j]);
            const uint32_t c8 = (j == 3) ? e * 8 : 0;
            sts16(pa + 16 * j, b); sts16(pb + 16 * j, b); sts16(pa + 16 * j + 10 + c8, b); sts16(pb + 16 * j + 10 + c8, b);
        }
    }
    {
        const uint32_t p = KS + PT3 + (36 + 36 * q + 9 * a + e) * 8;
        const uint32_t pa = p - (e ? 68 : 0), pb = p - (e ? 0 : 68);
        #pragma unroll
        for (int j = 0; j < 4; j++) {
            const uint16_t b = cvt_bf16(v3[j]);
            const int c = (j == 3) ? 26 : 18;
            if (j > 0 || lane != 0) { sts16(pa + 16 * j, b); sts16(pb + 16 * j, b); sts16(pa + 16 * j + c, b); sts16(pb + 16 * j + c, b); }
        }
    }
    if (lane == 0) {
        const uint16_t b = cvt_bf16(k2048);
        const uint32_t p = KS + PT3 + 180 * 8;
        sts16(p, b); sts16(p - 68, b); sts16(p + 18, b); sts16(p - 50, b);
        sts64(KS + TSC, (uint32_t)cvt_bf16(v3[0]), __float_as_uint(v2[0]));
    }
}

__host__ __device__ constexpr int tile_n(int b) { return b >= 0 ? b / 8 : -((7 - b) / 8); }
__host__ __device__ constexpr int tile_off(int b) { return tile_n(b) * NP + ((b - 8 * tile_n(b)) >> 2) * HB + ((b - 8 * tile_n(b)) & 3) * 32; }

template <int E0, int NE>
__device__ __forceinline__ void hconv(uint32_t U, uint32_t KS, int lane, uint32_t dbits, float (&aP)[NE][4], float (&aQ)[NE][4], float (&aR)[NE][4])
{
    const int g = lane >> 2, q = lane & 3;
    const uint32_t rowb = U + (lane & 7) * NP;
    const uint32_t ub = rowb + (lane >> 4) * 128 + ((lane >> 3) & 1) * 16;
    const uint32_t uq = rowb + (lane >> 3) * 16, uq2 = uq + (lane >> 4) * (HB - 128), uq3 = uq + (lane >> 4) * (NP - HB - 128);
    const uint32_t dA = (g == 2 * q) ? dbits : ((g == 2 * q + 1) ? (dbits << 16) : 0u);
    const uint32_t tb = KS + (g - 2 * q + 8) * 16;
    const uint32_t pb = KS + (((g + 1) >> 1) - 2 * q - 69 + 80) * 8;
    const uint32_t meta = (g & 1) ? 0x88888888u : 0xDDDDDDDDu;
    #pragma unroll
    for (int e = 0; e < NE; e++)
        #pragma unroll
        for (int k = 0; k < 4; k++) { aP[e][k] = 0.f; aQ[e][k] = 0.f; aR[e][k] = 0.f; }
    constexpr int B0 = E0 - 16;
    uint32_t xe[NE + 16][2], xo[NE + 16][2], xs[NE + 16][2];
    uint32_t qo[NE + 6][4], qe[NE + 6][4];
    auto ldtile = [&](int b) {
        const int i = b - B0;
        ldsm4(xe[i][0], xe[i][1], xo[i][0], xo[i][1], ub + tile_off(b));
        if (b < E0 - 9) { xs[i][0] = badd2(xe[i][0], xo[i][0]); xs[i][1] = badd2(xe[i][1], xo[i][1]); }
    };
    auto vadd = [](uint32_t x, uint32_t y) {
        uint32_t r; asm volatile("add.rn.bf16x2 %0, %1, %2;" : "=r"(r) : "r"(x), "r"(y)); return r;
    };
    auto ldquad = [&](int b) {
        const int i = b - B0;
        const int df = tile_off(b + 1) - tile_off(b);
        const uint32_t ad = ((df == 32) ? uq : (df == HB - 96 ? uq2 : uq3)) + tile_off(b);
        ldsm4(qe[i][0], qe[i][1], qe[i][2], qe[i][3], ad);
        ldsm4(qo[i][0], qo[i][1], qo[i][2], qo[i][3], ad + 128);
    };
    uint4 fE = lds128(tb + T4E), fQ = lds128(tb + T4Q), fR = lds128(tb + T4R);
    #pragma unroll
    for (int e = 0; e < NE; e++) ldtile(E0 + e);
    #pragma unroll
    for (int e = 0; e < NE; e++) {
        mma_bf16(aQ[e], dA, 0u, 0u, dA, xe[e + 16][0], xe[e + 16][1]);
        mma_bf16(aR[e], dA, 0u, 0u, dA, xo[e + 16][0], xo[e + 16][1]);
    }
    uint2 g1[4], g0[4], h1[4], h0[4];
    #pragma unroll
    for (int m = 0; m <= 16; m++) {
        const uint4 cE = fE;
        if (m < 16) ldtile(E0 - m - 1);
        if (m > 8 && m < 16) fE = lds128(tb + T4E + 256 * (m + 1));
        if (m == 16) {
            ldquad(E0 + NE - 11);
            #pragma unroll
            for (int k = 0; k < 4; k++) {
                g1[k] = lds64(pb + PQ + (16 * k + 8) * 8); g0[k] = lds64(pb + PQ + (16 * k) * 8);
                h1[k] = lds64(pb + PR + (16 * k + 8) * 8); h0[k] = lds64(pb + PR + (16 * k) * 8);
            }
        }
        #pragma unroll
        for (int e = 0; e < NE; e++) {
            const int i = e - m + 16;
            if (m <= 9) { xs[i][0] = vadd(xe[i][0], xo[i][0]); xs[i][1] = vadd(xe[i][1], xo[i][1]); }
            mma_bf16(aP[e], cE.x, cE.y, cE.z, cE.w, xs[i][0], xs[i][1]);
        }
        if (m <= 8) {
            fE = lds128(tb + T4E + 256 * (m + 1));
            #pragma unroll
            for (int e = 0; e < NE; e++) { const int i = e - m + 16; mma_bf16(aQ[e], fQ.x, fQ.y, fQ.z, fQ.w, xo[i][0], xo[i][1]); }
            if (m < 8) fQ = lds128(tb + T4Q + 256 * (m + 1));
            #pragma unroll
            for (int e = 0; e < NE; e++) { const int i = e - m + 16; mma_bf16(aR[e], fR.x, fR.y, fR.z, fR.w, xe[i][0], xe[i][1]); }
            if (m < 8) fR = lds128(tb + T4R + 256 * (m + 1));
        }
    }
    #pragma unroll
    for (int b = E0 + NE - 11; b >= E0 - 16; b--) {
        const int i = b - B0;
        if (b > E0 - 16) ldquad(b - 1);
        #pragma unroll
        for (int m = 10; m <= 16; m += 2) {
            const int e = b + m - E0;
            if (e >= 0 && e < NE) {
                const int k = (m - 10) >> 1;
                mma_sp(aQ[e], g1[k].x, g1[k].y, g0[k].x, g0[k].y, qo[i][0], qo[i][1], qo[i][2], qo[i][3], meta);
                mma_sp(aR[e], h1[k].x, h1[k].y, h0[k].x, h0[k].y, qe[i][0], qe[i][1], qe[i][2], qe[i][3], meta);
            }
        }
    }
}

template <int E0, int NE>
__device__ __forceinline__ void hfinal(uint32_t U, uint32_t KS, uint32_t W, int lane, float (&aP)[NE][4], float (&aQ)[NE][4], float (&aR)[NE][4])
{
    static_assert((E0 & 1) == 0 && (NE & 1) == 0, "tile pairs");
    const int g = lane >> 2, q = lane & 3;
    const uint32_t pb = W + P2_OFF + P2_PITCH * (2 * q - 2) + g * 16;
    const uint32_t sb = W + ST_OFF + 528 * 2 * q + g * 16;
    #pragma unroll
    for (int k = 0; k < 4; k++) {
        uint32_t o[NE];
        #pragma unroll
        for (int e = 0; e < NE; e += 2) {
            float y0 = aP[e][k] + aQ[e][k], y1 = aP[e][k] + aR[e][k], z0 = aP[e + 1][k] + aQ[e + 1][k], z1 = aP[e + 1][k] + aR[e + 1][k];
            if (q > 0) {
                const uint4 p = lds128(pb + P2_PITCH * (k & 1) + ((E0 + e) >> 1) * 256 + (k >> 1) * 128);
                y0 += __uint_as_float(p.x); y1 += __uint_as_float(p.y); z0 += __uint_as_float(p.z); z1 += __uint_as_float(p.w);
            }
            if (E0 + e == 6 && k == 3) {
                if (lane == 28) {
                    const float k512 = lds32f(KS + TSC + 4);
                    const float u0 = bf_lo(lds32(U)), u1 = bf_lo(lds32(U + 128));
                    z0 = fmaf(k512, u0, z0); z1 = fmaf(k512, u0 + u1, z1);
                }
            }
            o[e] = pack_bf16(y0, y1); o[e + 1] = pack_bf16(z0, z1);
        }
        #pragma unroll
        for (int e = 0; e < NE; e += 2) {
            const uint32_t a = sb + 528 * (k & 1) + ((E0 + e) >> 2) * 256 + (k >> 1) * 128;
            if (((E0 + e) & 3) == 0 && e + 4 <= NE) sts128(a, o[e], o[e + 1], o[e + 2], o[e + 3]);
            else if (!(((E0 + e) & 3) == 2 && e >= 2)) sts64(a + ((E0 + e) & 3) * 4, o[e], o[e + 1]);
        }
    }
}

__device__ __forceinline__ void s23(uint32_t W, uint32_t KS, int lane)
{
    const int g = lane >> 2, q = lane & 3;
    float acc[12][4];
    #pragma unroll
    for (int i = 0; i < 12; i++)
        #pragma unroll
        for (int k = 0; k < 4; k++) acc[i][k] = 0.f;
    const int k16 = lane & 15, mi = lane >> 3;
    {
        uint2 e1[5], e0[5], o1[5], o0[5];
        const int xi0 = g - 2 * q + 16;
        const uint32_t fb = KS + (xi0 + (xi0 >> 3)) * 8;
        #pragma unroll
        for (int d = 0; d < 5; d++) {
            e1[d] = lds64(fb + P2E + 144 * d); e0[d] = lds64(fb + P2E + 144 * d - 72);
            o1[d] = lds64(fb + P2O + 144 * d); o0[d] = lds64(fb + P2O + 144 * d - 72);
        }
        const uint32_t xb = W + ((mi >> 1) ? X3_OFF : X5_OFF) + (k16 & 1) * XH5 + ((k16 >> 1) + 1) * 16;
        {
            uint32_t b0, b1;
            ldsm2t(b0, b1, W + X5_OFF + (k16 == 15 ? XH5 : 0));
            #pragma unroll
            for (int d = 1; d <= 4; d++) mma_bf16(acc[d - 1], e1[d].x, e1[d].y, e0[d].x, e0[d].y, b0, b1);
        }
        #pragma unroll
        for (int kap = 0; kap < 12; kap++) {
            uint32_t x0, x1, y0, y1;
            ldsm4t(x0, x1, y0, y1, xb + kap * 128);
            #pragma unroll
            for (int d = 0; d <= 4; d++) if (kap + d < 12) mma_bf16(acc[kap + d], e1[d].x, e1[d].y, e0[d].x, e0[d].y, x0, x1);
            #pragma unroll
            for (int d = 0; d <= 4; d++) if (kap + d < 12) mma_bf16(acc[kap + d], o1[d].x, o1[d].y, o0[d].x, o0[d].y, y0, y1);
        }
    }
    {
        uint2 G9[9], G7[9];
        const int xi9 = 32 + 2 * ((g + 1) >> 1) - 4 * q, xi7 = 32 + 2 * (g >> 1) - 4 * q + 1;
        const uint32_t g9 = KS + PT3 + (xi9 + (xi9 >> 3)) * 8, g7 = KS + PT3 + (xi7 + (xi7 >> 3)) * 8;
        const uint32_t m9 = (g & 1) ? 0x88888888u : 0xDDDDDDDDu, m7 = (g & 1) ? 0xDDDDDDDDu : 0x88888888u;
        const uint32_t xb = W + X9_OFF + (lane & 1) * XH9 + (lane >> 1) * 16;
        uint2 A9[8][2], A7[8][2];
        #pragma unroll
        for (int D = 0; D < 8; D++) {
            A9[D][0] = lds64(g9 + 144 * D); A9[D][1] = lds64(g9 + 144 * D - 144);
            A7[D][0] = lds64(g7 + 144 * D); A7[D][1] = lds64(g7 + 144 * D - 144);
        }
        (void)G9; (void)G7;
        #pragma unroll
        for (int kp = 0; kp < 4; kp++) {
            uint32_t b[4], c[4];
            ldsm4t(b[0], b[1], b[2], b[3], xb + kp * 256);
            ldsm4t(c[0], c[1], c[2], c[3], xb + (X7_OFF - X9_OFF) + kp * 256);
            #pragma unroll
            for (int rp = 2 * kp; rp < 8; rp++) {
                const int D = rp - 2 * kp;
                mma_sp(acc[rp + 4], A9[D][0].x, A9[D][0].y, A9[D][1].x, A9[D][1].y, b[0], b[1], b[2], b[3], m9);
            }
            #pragma unroll
            for (int rp = 2 * kp; rp < 8; rp++) {
                const int D = rp - 2 * kp;
                mma_sp(acc[rp + 4], A7[D][0].x, A7[D][0].y, A7[D][1].x, A7[D][1].y, c[0], c[1], c[2], c[3], m7);
            }
        }
    }
    {
        const uint32_t kk = lds32(KS + TSC);
        const uint32_t ad = (g == 2 * q) ? kk : ((g == 2 * q + 1) ? (kk << 16) : 0u);
        const uint32_t xb = W + XV_OFF + (k16 & 1) * XH9 + ((k16 >> 1) + 1) * 16;
        #pragma unroll
        for (int rho = 3; rho < 12; rho++) {
            uint32_t b0, b1;
            ldsm2t(b0, b1, rho == 3 ? (W + XV_OFF + (k16 == 15 ? XH9 : 0)) : (xb + (rho - 4) * 128));
            mma_bf16(acc[rho], ad, 0u, 0u, ad, b0, b1);
        }
    }
    __syncwarp();
    const uint32_t pb = W + P2_OFF + (((g >> 1) & 1) * 32 + (4 * (g & 1) + 2 * (q & 1)) * 4 + (g >> 2) * 2 + (q >> 1)) * 4;
    #pragma unroll
    for (int rho = 0; rho < 12; rho++) {
        const uint32_t a = pb + (rho >> 1) * P2_PITCH + (rho & 1) * 512;
        sts32f(a, acc[rho][0]); sts32f(a + 16, acc[rho][1]);
        sts32f(a + 256, acc[rho][2]); sts32f(a + 256 + 16, acc[rho][3]);
    }
}

template <bool FULL>
__device__ __forceinline__ void wgen_pass(uint32_t U, uint32_t W, int lam, int lane)
{
    const uint32_t a0 = U + (lam >> 4) * NP + ((lane >> 3) & 1) * HB + (lane & 7) * 16;
    const uint32_t aL = a0 - ((lane & 7) ? 8 : ((lane & 8) ? HB - 120 : NP - HB - 120));
    const uint32_t aR = a0 + (((lane & 7) != 7) ? 16 : ((lane & 8) ? NP - HB - 112 : HB - 112));
    uint32_t e[7], o[7];
    { uint2 t = lds64(aL); e[0] = t.x; e[1] = t.y; }
    { uint4 t = lds128(a0); e[2] = t.x; e[3] = t.y; e[4] = t.z; e[5] = t.w; }
    e[6] = lds32(aR);
    { uint2 t = lds64(aL + 128); o[0] = t.x; o[1] = t.y; }
    { uint4 t = lds128(a0 + 128); o[2] = t.x; o[3] = t.y; o[4] = t.z; o[5] = t.w; }
    o[6] = lds32(aR + 128);
    uint32_t sA[7], sB[6], eB[6], oB[5];
    #pragma unroll
    for (int w = 1; w < 7; w++) sA[w] = badd2(e[w], o[w]);
    #pragma unroll
    for (int w = 1; w < 6; w++) { sB[w] = shift1(sA[w], sA[w + 1]); eB[w] = shift1(e[w], e[w + 1]); }
    #pragma unroll
    for (int w = 0; w < 5; w++) oB[w] = shift1(o[w], o[w + 1]);
    uint32_t x5e[4], x5o[4], x3e[4], x3o[4], x7e[4], x7o[4], x9e[4], x9o[4], xve[4];
    #pragma unroll
    for (int k = 0; k < 4; k++) {
        const int w = k + 2;
        const uint32_t d1 = badd2(sB[w - 1], sA[w]), d2 = badd2(sA[w], sB[w]);
        x5e[k] = badd2(d1, eB[w]); x5o[k] = badd2(oB[w - 1], d2);
        x3e[k] = badd2(oB[w - 2], sA[w - 1]); x3o[k] = badd2(sA[w - 1], eB[w - 1]);
        if (FULL) {
            const uint32_t t3 = badd2(d1, sB[w]);
            x7e[k] = badd2(o[w - 1], t3); x7o[k] = badd2(t3, e[w + 1]);
            x9e[k] = badd2(sA[w - 1], x7o[k]); x9o[k] = badd2(x7e[k], sA[w + 1]);
            xve[k] = badd2(sA[w - 1], x5e[k]);
        }
    }
    const uint32_t w5 = W + (lam + 1) * 16;
    sts128(w5 + X5_OFF, x5e[0], x5e[1], x5o[0], x5o[1]); sts128(w5 + X5_OFF + XH5, x5e[2], x5e[3], x5o[2], x5o[3]);
    sts128(w5 + X3_OFF, x3e[0], x3e[1], x3o[0], x3o[1]); sts128(w5 + X3_OFF + XH5, x3e[2], x3e[3], x3o[2], x3o[3]);
    if (FULL) {
        sts128(w5 + XV_OFF, xve[0], xve[1], x7e[0], x7e[1]); sts128(w5 + XV_OFF + XH9, xve[2], xve[3], x7e[2], x7e[3]);
        sts128(w5 - 16 + X9_OFF + XH9, x9e[0], x9e[1], x9o[0], x9o[1]);
        sts128(w5 - 16 + X7_OFF + XH9, x7e[0], x7e[1], x7o[0], x7o[1]);
        if (lam < 63) {
            sts128(w5 + X9_OFF, x9e[2], x9e[3], x9o[2], x9o[3]);
            sts128(w5 + X7_OFF, x7e[2], x7e[3], x7o[2], x7o[3]);
        }
    }
}

__device__ __forceinline__ void wgen(uint32_t U, uint32_t W, int lane)
{
    wgen_pass<true>(U, W, lane, lane);
    wgen_pass<true>(U, W, lane + 32, lane);
    wgen_pass<false>(U, W, lane + 64, lane);
    if (lane == 0) {
        const uint32_t e0 = lds32(U), o0 = lds32(U + 128);
        const uint32_t s0 = badd2(e0, o0);
        const uint32_t a = e0 << 16, b = s0 << 16;
        const uint32_t c = badd2(b, __byte_perm(s0, e0, 0x7610));
        const uint32_t d = badd2(b, s0);
        sts128(W + X5_OFF + XH5, 0u, a, 0u, b);
        sts128(W + XV_OFF + XH9, 0u, a, 0u, b);
        sts128(W + X9_OFF, 0u, __byte_perm(e0, c, 0x7610), 0u, d);
        sts128(W + X7_OFF, 0u, b, 0u, __byte_perm(e0, c, 0x7610));
        sts128(W + X5_OFF, 0u, 0u, 0u, 0u);
        sts128(W + XV_OFF, 0u, 0u, 0u, 0u);
    }
}

__device__ __forceinline__ void out8(uint32_t sb, __nv_bfloat16* __restrict__ out, uint32_t rank, int chbase, int lh, int lane, int i0)
{
    const int mj = lane >> 3, mi = lane & 7, g = lane >> 2, q = lane & 3;
    const uint32_t ya = sb + YIN_OFF + mi * YP + 4 * 512 + lh * 256 + mj * 16 + i0 * 64;
    __nv_bfloat16* op = out + (size_t)(RPC * rank + 128 * lh + 32 * (g >> 1) + (g & 1) + 8 * i0) * D_ + chbase + 32 + 2 * q;
    uint32_t y[2][4];
    ldsm4t(y[0][0], y[0][1], y[0][2], y[0][3], ya);
    ldsm4t(y[1][0], y[1][1], y[1][2], y[1][3], ya + 64);
    #pragma unroll
    for (int i = 0; i < 2; i++)
        #pragma unroll
        for (int k = 0; k < 4; k++)
            asm volatile("st.global.u32 [%0], %1;" ::"l"(op + (size_t)(2 * (4 * i + k)) * D_), "r"(y[i][k]) : "memory");
}

#define NEK4 6
#define WWAIT 0
#define STAG4 4
#define UDELAY 400
#define LMASK_ 0x2EF
constexpr uint32_t LMASK = LMASK_;
constexpr int NLD = __builtin_popcount(LMASK) >= 8 ? 8 : 4, CPL = 16 / NLD;

__global__ void __launch_bounds__(384, 1)
ssm_kernel(const __nv_bfloat16* __restrict__ u, const __nv_bfloat16* __restrict__ A_re, const __nv_bfloat16* __restrict__ A_im,
           const __nv_bfloat16* __restrict__ B_re, const __nv_bfloat16* __restrict__ B_im, const __nv_bfloat16* __restrict__ C_re,
           const __nv_bfloat16* __restrict__ C_im, const __nv_bfloat16* __restrict__ log_dt, const __nv_bfloat16* __restrict__ Dsk,
           __nv_bfloat16* __restrict__ out)
{
    extern __shared__ __align__(128) unsigned char smem[];
    const uint32_t sb = smem_u32(smem);
    const int tid = threadIdx.x, lane = tid & 31;
    const int w = __shfl_sync(0xffffffffu, tid >> 5, 0);
    uint32_t rank; asm("mov.u32 %0, %%cluster_ctarank;" : "=r"(rank));
    const int chbase = min((int)(blockIdx.x / CL) * GCH, D_ - GCH);
    const int h = (w == 9) || (w < 8 && !(w & 2));
    const int slot = (w >= 8) ? 4 : ((w & 1) | ((w >> 2) << 1));
    const int ch = chbase + ((slot < 4) ? 8 * (rank >> 1) + 2 * slot + (rank & 1) : 32 + rank);
    const int g = lane >> 2, q = lane & 3;

    TLG(15); TL(0);
    uint32_t pv[6], ldtb, dbits;
    {
        const int o = ch * N_ + 64 * h + 2 * lane;
        ldtb = __ldg(reinterpret_cast<const unsigned short*>(log_dt + ch));
        pv[0] = __ldg(reinterpret_cast<const uint32_t*>(A_re + o));
        pv[1] = __ldg(reinterpret_cast<const uint32_t*>(A_im + o));
        pv[2] = __ldg(reinterpret_cast<const uint32_t*>(B_re + o));
        pv[3] = __ldg(reinterpret_cast<const uint32_t*>(B_im + o));
        pv[4] = __ldg(reinterpret_cast<const uint32_t*>(C_re + o));
        pv[5] = __ldg(reinterpret_cast<const uint32_t*>(C_im + o));
        dbits = __ldg(reinterpret_cast<const unsigned short*>(Dsk + ch));
    }
    constexpr int CPL = 4;
    const bool isld = w >= 8;
    const int lh = w & 1, c0 = 8 * lh + 4 * ((w >> 1) & 1);
    uint4 ur[CPL][2]; uint32_t uv[CPL][2];
    if (isld) {
        { const long long t0 = clock64(); while (clock64() - t0 < UDELAY) { } }
        const __nv_bfloat16* p = u + (size_t)(RPC * rank + 16 * c0 + 2 * g) * D_ + chbase;
        #pragma unroll
        for (int c = 0; c < CPL; c++)
            #pragma unroll
            for (int par = 0; par < 2; par++) {
                ur[c][par] = __ldg(reinterpret_cast<const uint4*>(p + (16 * c + par) * D_ + 8 * q));
                uv[c][par] = __ldg(reinterpret_cast<const uint32_t*>(p + (16 * c + par) * D_ + 32 + 2 * q));
            }
    }
    if (tid == 0) {
        mbar_init(sb + MB_U, 1);
        mbar_init(sb + MB_Y, 1); mbar_init(sb + MB_Y + 8, 1);
        asm volatile("fence.mbarrier_init.release.cluster;" ::: "memory");
        mbar_arrive_tx(sb + MB_U, NS * 4096);
        mbar_arrive_tx(sb + MB_Y, 32 * RPC * 2); mbar_arrive_tx(sb + MB_Y + 8, 8 * RPC * 2);
    }
    cl_arrive();
    const uint32_t U = sb + 2 * NP + slot * 256, W = sb + UB_SIZE + slot * SLOT, KS = W + W_SIZE;
    sts128(sb + (h ? NP : 0) + (lane >> 4) * HB + slot * 256 + (lane & 15) * 16, 0u, 0u, 0u, 0u);
    TL(1);
    if (isld) {
        const int mj = lane >> 3, mi = lane & 7;
        const uint32_t a = sb + YIN_OFF + mi * YP + lh * HB + (c0 & 7) * 16;
        #pragma unroll
        for (int c = 0; c < CPL; c++)
            #pragma unroll
            for (int par = 0; par < 2; par++)
                stsm4t(a + mj * 256 + par * 128 + c * 16, ur[c][par].x, ur[c][par].y, ur[c][par].z, ur[c][par].w);
        #pragma unroll
        for (int c = 0; c < CPL; c += 2)
            stsm4t(a + 4 * 256 + (mj & 1) * 128 + (c + (mj >> 1)) * 16, uv[c][0], uv[c][1], uv[c + 1][0], uv[c + 1][1]);
        asm volatile("fence.proxy.async.shared::cta;" ::: "memory");
        if (w < 10) asm volatile("bar.arrive %0, 64;" ::"r"(12 + lh) : "memory");
        else {
            asm volatile("bar.sync %0, 64;" ::"r"(12 + lh) : "memory");
            TL(2);
            cl_wait();
            if (elect_one()) {
                const uint32_t dst = sb + (2 + rank) * NP + lh * HB;
                #pragma unroll
                for (int r = 0; r < CL; r++) bulk_s2c(mapa(dst, r), sb + YIN_OFF + r * YP + lh * HB, HB, mapa(sb + MB_U, r));
            }
            __syncwarp();
            TL(3);
            cl_arrive();
            cl_wait();
            mbar_wait(sb + MB_Y + 8, 0);
            cl_arrive();
            TL(10);
            out8(sb, out, rank, chbase, lh, lane, 0);
            TL(11);
            cl_wait();
            TL(12); TLG(14);
            return;
        }
    }
    const bool grpB = (slot & 6) == 2;
    if (grpB) asm volatile("bar.sync 14, 256;" ::: "memory");
    TL(13);
    const uint32_t S = h ? W : KS;
    float isc, gmax;
    prep(S, lane, pv, ldtb, isc, gmax);
    if (slot < 2) asm volatile("bar.arrive 14, 256;" ::: "memory");
    TL(3);
    float acc[2][3][4];
    kmma(S, lane, isc, gmax, acc);
    TL(4);
    const int idX = 1 + 2 * slot, idY = 2 + 2 * slot;
    if (h == 0) {
        sts128(KS + XK + lane * 16, __float_as_uint(acc[0][1][1]), __float_as_uint(acc[0][1][3]), __float_as_uint(acc[1][1][1]), __float_as_uint(acc[1][1][3]));
        sts128(KS + XK + 512 + lane * 16, __float_as_uint(acc[0][2][0]), __float_as_uint(acc[0][2][2]), __float_as_uint(acc[1][2][0]), __float_as_uint(acc[1][2][2]));
        if (lane == 0) sts32f(KS + XK + 1024, acc[0][2][1]);
        nb_sync(idX);
        const uint4 t0 = lds128(KS + XW + lane * 16), t1 = lds128(KS + XW + 512 + lane * 16), t2 = lds128(KS + XW + 1024 + lane * 16);
        const float k512 = shf(acc[0][1][1], 0) + lds32f(KS + XW + 1536);
        float fe[4], fo[4], fu[4];
        fe[0] = acc[0][0][0] + __uint_as_float(t0.x); fe[1] = acc[0][0][2] + __uint_as_float(t0.y);
        fe[2] = acc[1][0][0] + __uint_as_float(t0.z); fe[3] = acc[1][0][2] + __uint_as_float(t0.w);
        fo[0] = acc[0][0][1] + __uint_as_float(t1.x); fo[1] = acc[0][0][3] + __uint_as_float(t1.y);
        fo[2] = acc[1][0][1] + __uint_as_float(t1.z); fo[3] = acc[1][0][3] + __uint_as_float(t1.w);
        fu[0] = acc[0][1][0] + __uint_as_float(t2.x); fu[1] = acc[0][1][2] + __uint_as_float(t2.y);
        fu[2] = acc[1][1][0] + __uint_as_float(t2.z); fu[3] = acc[1][1][2] + __uint_as_float(t2.w);
        ktables(KS, lane, fe, fo, fu, k512);
        if (slot == 4) nb_arrive(idX);
        __syncwarp();
        TL(5);
        cl_wait();
        mbar_wait(sb + MB_U, 0);
        cl_arrive();
        TL(6);
        if (slot == 4) {
            float aP[NEK4][4], aQ[NEK4][4], aR[NEK4][4];
            hconv<0, NEK4>(U, KS, lane, dbits, aP, aQ, aR);
            TL(7);
            nb_sync(idY);
            hfinal<0, NEK4>(U, KS, W, lane, aP, aQ, aR);
            asm volatile("fence.proxy.async.shared::cta;" ::: "memory");
            nb_arrive(idX);
            TL(8);
            cl_wait();
            if (elect_one()) {
                const uint32_t dst = sb + YIN_OFF + rank * YP + 4 * 512;
                #pragma unroll
                for (int n = 0; n < 8; n++) bulk_s2c(mapa(dst, n), W + ST_OFF + 528 * n, 256, mapa(sb + MB_Y + 8, n));
            }
            __syncwarp();
        } else
        {
            float aP[8][4], aQ[8][4], aR[8][4];
            hconv<0, 8>(U, KS, lane, dbits, aP, aQ, aR);
            TL(7);
            nb_sync(idY);
            hfinal<0, 8>(U, KS, W, lane, aP, aQ, aR);
            asm volatile("fence.proxy.async.shared::cta;" ::: "memory");
            __syncwarp();
            TL(8);
            cl_wait();
            if (elect_one()) {
                const uint32_t dst = sb + YIN_OFF + rank * YP + slot * 512;
                const uint32_t mb = sb + MB_Y + ((slot == 4) ? 8 : 0);
                #pragma unroll
                for (int n = 0; n < 8; n++) bulk_s2c(mapa(dst, n), W + ST_OFF + 528 * n, 512, mapa(mb, n));
            }
            __syncwarp();
        }
    } else {
        sts128(KS + XW + lane * 16, __float_as_uint(acc[0][0][0]), __float_as_uint(acc[0][0][2]), __float_as_uint(acc[1][0][0]), __float_as_uint(acc[1][0][2]));
        sts128(KS + XW + 512 + lane * 16, __float_as_uint(acc[0][0][1]), __float_as_uint(acc[0][0][3]), __float_as_uint(acc[1][0][1]), __float_as_uint(acc[1][0][3]));
        sts128(KS + XW + 1024 + lane * 16, __float_as_uint(acc[0][1][0]), __float_as_uint(acc[0][1][2]), __float_as_uint(acc[1][1][0]), __float_as_uint(acc[1][1][2]));
        if (lane == 0) sts32f(KS + XW + 1536, acc[0][1][1]);
        nb_sync(idX);
        const uint4 t0 = lds128(KS + XK + lane * 16), t1 = lds128(KS + XK + 512 + lane * 16);
        const float k2048 = acc[0][2][1] + lds32f(KS + XK + 1024);
        float v2[4], v3[4];
        v2[0] = acc[0][1][1] + __uint_as_float(t0.x); v2[1] = acc[0][1][3] + __uint_as_float(t0.y);
        v2[2] = acc[1][1][1] + __uint_as_float(t0.z); v2[3] = acc[1][1][3] + __uint_as_float(t0.w);
        v3[0] = acc[0][2][0] + __uint_as_float(t1.x); v3[1] = acc[0][2][2] + __uint_as_float(t1.y);
        v3[2] = acc[1][2][0] + __uint_as_float(t1.z); v3[3] = acc[1][2][2] + __uint_as_float(t1.w);
        wtables(KS, lane, v2, v3, k2048);
        TL(5);
        cl_wait();
        mbar_wait(sb + MB_U, 0);
        cl_arrive();
        TL(6);
        wgen(U, W, lane);
        __syncwarp();
        s23(W, KS, lane);
        if (slot == 4) {
            nb_sync(idX);
            nb_arrive(idY);
            TL(7);
            float aP[8 - NEK4][4], aQ[8 - NEK4][4], aR[8 - NEK4][4];
            hconv<NEK4, 8 - NEK4>(U, KS, lane, dbits, aP, aQ, aR);
            hfinal<NEK4, 8 - NEK4>(U, KS, W, lane, aP, aQ, aR);
            asm volatile("fence.proxy.async.shared::cta;" ::: "memory");
            nb_sync(idX);
            TL(8);
            cl_wait();
            if (elect_one()) {
                const uint32_t dst = sb + YIN_OFF + rank * YP + 4 * 512 + 256;
                #pragma unroll
                for (int n = 0; n < 8; n++) bulk_s2c(mapa(dst, n), W + ST_OFF + 528 * n + 256, 256, mapa(sb + MB_Y + 8, n));
            }
            __syncwarp();
        } else
        {
            nb_arrive(idY);
            TL(7);
            cl_wait();
        }
    }
    {
        TL(9);
        const int mj = lane >> 3, mi = lane & 7;
        if (w < 8) {
            mbar_wait(sb + MB_Y, 0);
            cl_arrive();
            TL(10);
            const uint32_t ya = sb + YIN_OFF + mi * YP + mj * 512 + w * 64;
            __nv_bfloat16* op = out + (size_t)(RPC * rank + 128 * (w >> 2) + 16 * ((w >> 1) & 1) + 8 * (w & 1) + 32 * (g >> 1) + (g & 1)) * D_ + chbase + 8 * q;
            #pragma unroll
            for (int i = 0; i < 4; i++) {
                uint32_t y0, y1, y2, y3;
                ldsm4t(y0, y1, y2, y3, ya + i * 16);
                asm volatile("st.global.v4.u32 [%0], {%1,%2,%3,%4};" ::"l"(op + (size_t)i * 2 * D_), "r"(y0), "r"(y1), "r"(y2), "r"(y3) : "memory");
            }
        } else {
            mbar_wait(sb + MB_Y + 8, 0);
            cl_arrive();
            TL(10);
            out8(sb, out, rank, chbase, w & 1, lane, 2);
        }
    }
    TL(11);
    cl_wait();
    TL(12); TLG(14);
}

__device__ float g_kscr[D_ * L_];
__global__ void fb_kgen(const __nv_bfloat16* __restrict__ A_re, const __nv_bfloat16* __restrict__ A_im, const __nv_bfloat16* __restrict__ B_re,
                        const __nv_bfloat16* __restrict__ B_im, const __nv_bfloat16* __restrict__ C_re, const __nv_bfloat16* __restrict__ C_im,
                        const __nv_bfloat16* __restrict__ log_dt)
{
    const int d = blockIdx.y, l = blockIdx.x * blockDim.x + threadIdx.x;
    const float dt = __bfloat162float(__float2bfloat16_rn(expf(__bfloat162float(log_dt[d]))));
    const float lf = __bfloat162float(__float2bfloat16_rn((float)l));
    float acc = 0.f;
    for (int n = 0; n < N_; n++) {
        const int o = d * N_ + n;
        const float zr = dt * __bfloat162float(A_re[o]), zi = dt * __bfloat162float(A_im[o]);
        const float br = dt * __bfloat162float(B_re[o]), bi = dt * __bfloat162float(B_im[o]);
        const float cr = __bfloat162float(C_re[o]), ci = __bfloat162float(C_im[o]);
        float sn, cs; sincosf(zi * lf, &sn, &cs);
        const float m = expf(zr * lf);
        acc += m * ((cr * br - ci * bi) * cs - (cr * bi + ci * br) * sn);
    }
    g_kscr[d * L_ + l] = acc;
}
__global__ void fb_conv(const __nv_bfloat16* __restrict__ u, const __nv_bfloat16* __restrict__ Dsk, __nv_bfloat16* __restrict__ out)
{
    const int d = blockIdx.y * blockDim.x + threadIdx.x, t = blockIdx.x;
    float y = 0.f;
    for (int l = 0; l <= t; l++) y = fmaf(g_kscr[d * L_ + l], __bfloat162float(u[(size_t)(t - l) * D_ + d]), y);
    const float sk = __bfloat162float(__float2bfloat16_rn(__bfloat162float(u[(size_t)t * D_ + d]) * __bfloat162float(Dsk[d])));
    out[(size_t)t * D_ + d] = __float2bfloat16_rn(__bfloat162float(__float2bfloat16_rn(y)) + sk);
}

}

extern "C" void kernel_launch(void* const* d_in, const int* in_sizes, int n_in, void* d_out, int out_size)
{
    static int mode = -1;
    static cudaLaunchConfig_t cfg;
    static cudaLaunchAttribute at[1];
    if (mode < 0) {
        mode = 1;
        if (cudaFuncSetAttribute(ssm_kernel, cudaFuncAttributeMaxDynamicSharedMemorySize, SMEM_BYTES) == cudaSuccess &&
            cudaFuncSetAttribute(ssm_kernel, cudaFuncAttributeNonPortableClusterSizeAllowed, 1) == cudaSuccess) {
            cfg = cudaLaunchConfig_t{};
            cfg.gridDim = dim3(NCL * CL); cfg.blockDim = dim3(384); cfg.dynamicSmemBytes = SMEM_BYTES; cfg.stream = cudaStreamPerThread;
            at[0].id = cudaLaunchAttributeClusterDimension;
            at[0].val.clusterDim.x = CL; at[0].val.clusterDim.y = 1; at[0].val.clusterDim.z = 1;
            cfg.attrs = at; cfg.numAttrs = 1;
            int nc = 0;
            if (cudaOccupancyMaxActiveClusters(&nc, ssm_kernel, &cfg) == cudaSuccess && nc >= 1) mode = 0;
        }
        cudaGetLastError();
    }
    const __nv_bfloat16* p[9];
    for (int i = 0; i < 9; i++) p[i] = (const __nv_bfloat16*)d_in[i];
    if (mode == 0)
        cudaLaunchKernelEx(&cfg, ssm_kernel, p[0], p[1], p[2], p[3], p[4], p[5], p[6], p[7], p[8], (__nv_bfloat16*)d_out);
    else {
        fb_kgen<<<dim3(L_ / 256, D_), 256, 0, cudaStreamPerThread>>>(p[1], p[2], p[3], p[4], p[5], p[6], p[7]);
        fb_conv<<<dim3(L_, D_ / 192), 192, 0, cudaStreamPerThread>>>(p[0], p[8], (__nv_bfloat16*)d_out);
    }
}
```
